```python
import torch

def _softmax(x, axis=-1):
    return torch.softmax(x, dim=axis)
def _gelu(x):
    return torch.nn.functional.gelu(x, approximate="tanh")
def _silu(x):
    return torch.nn.functional.silu(x)
def _sigmoid(x):
    return torch.sigmoid(x)
def _layernorm(x, axis=-1, eps=1e-5):
    m = x.mean(dim=axis, keepdim=True)
    v = x.var(dim=axis, keepdim=True, unbiased=False)
    return (x - m) / torch.sqrt(v + eps)
def _scatter_add(tgt, idx, src, axis=0):
    return tgt.clone().index_add_(axis, idx, src)
def _segment_sum(src, seg, n):
    out = torch.zeros((n,) + src.shape[1:], dtype=src.dtype)
    return out.index_add_(0, seg, src)
def _pad(x, pw):
    flat = tuple(v for pair in reversed(pw) for v in pair)
    return torch.nn.functional.pad(x, flat)

kernel_name = 'recurrent_scan__sliding_local_dilated__swiglu_ffn__prompt'

def setup_inputs():

    _w = (lambda a: (lambda t: t.to(torch.bfloat16) if t.is_floating_point() else t)(torch.as_tensor(a)))
    def _A_setup():
        B, S, D = 1, 2048, 448
        return {
            "x": _w((lambda *s: torch.randn(*s, dtype=torch.bfloat16) * 0.05)(B, S, D)),
            "wqkv": _w((lambda *s: torch.randn(*s, dtype=torch.bfloat16) * 0.05)(D, 3 * D)),
            "wo": _w((lambda *s: torch.randn(*s, dtype=torch.bfloat16) * 0.05)(D, D)),
        }
    _A_in = _A_setup()

    def _B_setup():
        B, S, D, F = 1, 2048, 448, 1792
        return {
            "x": _w((lambda *s: torch.randn(*s, dtype=torch.bfloat16) * 0.05)(B, S, D)),
            "w_gate": _w((lambda *s: torch.randn(*s, dtype=torch.bfloat16) * 0.05)(D, F)),
            "w_up": _w((lambda *s: torch.randn(*s, dtype=torch.bfloat16) * 0.05)(D, F)),
            "w_down": _w((lambda *s: torch.randn(*s, dtype=torch.bfloat16) * 0.05)(F, D)),
        }
    _B_in = _B_setup()

    return {
        "A_x": _A_in["x"],
        "A_wqkv": _A_in["wqkv"],
        "A_wo": _A_in["wo"],
        "B_x": _B_in["x"],
        "B_w_gate": _B_in["w_gate"],
        "B_w_up": _B_in["w_up"],
        "B_w_down": _B_in["w_down"],
    }

def reference(A_x, A_wqkv, A_wo, B_x, B_w_gate, B_w_up, B_w_down):
    def _A_ref(x, wqkv, wo):
        B, S, D = x.shape
        H = 16; Dh = D // H
        W, dil = 8, 2
        qkv = (lambda x, *d: x.permute(*d))((x @ wqkv).reshape(B, S, 3, H, Dh), 2, 0, 3, 1, 4)
        q, k, v = qkv[0], qkv[1], qkv[2]
        scale = Dh ** -0.5
        pos = torch.arange(S)
        off = torch.arange(W) * dil
        idx = pos[:, None] - off[None, :]
        mask = idx >= 0
        idx_c = torch.where(mask, idx, 0).reshape(-1)
        kg = k[:, :, idx_c, :].reshape(B, H, S, W, Dh)
        vg = v[:, :, idx_c, :].reshape(B, H, S, W, Dh)
        logits = torch.einsum("bhsd,bhswd->bhsw", q, kg) * scale
        logits = torch.where(mask[None, None, :, :], logits, -1e9)
        attn = _softmax(logits, axis=-1)
        o = torch.einsum("bhsw,bhswd->bhsd", attn, vg)
        return (lambda x, *d: x.permute(*d))(o, 0, 2, 1, 3).reshape(B, S, D) @ wo

    def _B_ref(x, w_gate, w_up, w_down):
        g = _silu(x @ w_gate)
        u = x @ w_up
        return (g * u) @ w_down

    x = A_x
    xn = _layernorm(x, axis=-1)
    s = _A_ref(xn, A_wqkv, A_wo)
    g = _silu(_B_ref(xn, B_w_gate, B_w_up, B_w_down))
    return x + s * g
```

```cpp
#include <cuda_runtime.h>
#include <cuda_bf16.h>
#include <cuda.h>
#include <stdint.h>

namespace {

constexpr int S_ = 2048, D_ = 448, F_ = 1792;
constexpr int NST = 10;
constexpr int STAGE = 16384;
constexpr int KVB = 18 * 896;
constexpr int OFF_K = NST * STAGE;
constexpr int OFF_V = OFF_K + KVB;
constexpr int OFF_Q = OFF_V + KVB;
constexpr int OFF_HS = OFF_Q + 16384;
constexpr int OFF_PART = OFF_K;
constexpr int OFF_BAR = 229376;
constexpr int SMEM_BYTES = OFF_BAR + 1024;
constexpr int B_FULL = 0, B_EMPTY = 10, B_KV = 20, B_Q = 21  , B_H = 23  , B_HFREE = 25  ,
              B_PART = 27  , B_KVFREE = 29, B_HALO = 30, B_GO = 31, B_XFREE = 32, B_X = 33  , B_WOK = 47;
#define LAG0 2
#define LAGA 6
#define LAGB 6
#define LAGD 4

struct Params {
  CUtensorMap xm, wqkv, wg, wu, wg32, wu32, outm;
  const __nv_bfloat16* x;
  const uint4* wd;
  const uint4* wo;
};

__device__ uint4 g_h[S_ * F_ / 8];
__device__ uint4 g_o[S_ * D_ / 8];
__device__ uint4 g_wd[F_ * D_ / 8];
__device__ uint4 g_wo[D_ * D_ / 8];
__device__ uint32_t g_wflag[8];
__device__ uint4 g_halo[16 * 8 * 224];
__device__ uint32_t g_hflag[16 * 2 * 14 * 8];
__device__ uint32_t g_oflag[16 * 8];
__device__ uint32_t g_haloflag[16 * 8 * 8];
__device__ uint32_t g_epoch[128 * 8];
#define TS(slot)
#define TG(slot)
#define TSW(slot)

__device__ __forceinline__ uint32_t s2u(const void* p) { return (uint32_t)__cvta_generic_to_shared(p); }
__device__ __forceinline__ void mbar_init(uint32_t b, int c) { asm volatile("mbarrier.init.shared::cta.b64 [%0], %1;" ::"r"(b), "r"(c) : "memory"); }
__device__ __forceinline__ void mbar_expect(uint32_t b, int bytes) { asm volatile("mbarrier.arrive.expect_tx.shared::cta.b64 _, [%0], %1;" ::"r"(b), "r"(bytes) : "memory"); }
__device__ __forceinline__ void mbar_arrive(uint32_t b) { asm volatile("mbarrier.arrive.shared::cta.b64 _, [%0];" ::"r"(b) : "memory"); }
__device__ __forceinline__ void mbar_arrive_cluster(uint32_t b) { asm volatile("mbarrier.arrive.shared::cluster.b64 _, [%0];" ::"r"(b) : "memory"); }
__device__ __forceinline__ uint32_t mapa(uint32_t a, uint32_t r) { uint32_t o; asm volatile("mapa.shared::cluster.u32 %0, %1, %2;" : "=r"(o) : "r"(a), "r"(r)); return o; }
__device__ __forceinline__ void mbar_wait(uint32_t b, uint32_t ph) {
  uint32_t ok;
  asm volatile("{.reg .pred p; mbarrier.try_wait.parity.shared::cta.b64 p, [%1], %2; selp.u32 %0,1,0,p;}" : "=r"(ok) : "r"(b), "r"(ph) : "memory");
  if (ok) return;
  int it = 0;
  do {
    asm volatile("{.reg .pred p; mbarrier.try_wait.parity.shared::cta.b64 p, [%1], %2; selp.u32 %0,1,0,p;}" : "=r"(ok) : "r"(b), "r"(ph) : "memory");
    if (++it > (1 << 18)) __trap();
  } while (!ok);
}
__device__ __forceinline__ uint32_t ld_flag(const uint32_t* f) { uint32_t v; asm volatile("ld.relaxed.gpu.global.u32 %0, [%1];" : "=r"(v) : "l"(f) : "memory"); return v; }
__device__ __forceinline__ void flag_add(uint32_t* f) { asm volatile("red.relaxed.gpu.global.add.u32 [%0], 1;" ::"l"(f) : "memory"); }
__device__ __forceinline__ void flag_add_rel(uint32_t* f) { asm volatile("red.release.gpu.global.add.u32 [%0], 1;" ::"l"(f) : "memory"); }
__device__ __forceinline__ void fence_async_smem() { asm volatile("fence.proxy.async.shared::cta;" ::: "memory"); }
__device__ __forceinline__ void fence_async_global() { asm volatile("fence.proxy.async.global;" ::: "memory"); }

__device__ __forceinline__ void tma2d(uint32_t dst, const CUtensorMap* m, uint32_t bar, int c0, int c1) {
  asm volatile("cp.async.bulk.tensor.2d.shared::cluster.global.mbarrier::complete_tx::bytes [%0], [%1, {%3,%4}], [%2];" ::"r"(dst), "l"(m), "r"(bar), "r"(c0), "r"(c1) : "memory");
}
__device__ __forceinline__ void tma2d_mc(uint32_t dst, const CUtensorMap* m, uint32_t bar, int c0, int c1) {
  asm volatile("cp.async.bulk.tensor.2d.shared::cluster.global.mbarrier::complete_tx::bytes.multicast::cluster [%0], [%1, {%3,%4}], [%2], %5;" ::"r"(dst), "l"(m), "r"(bar), "r"(c0), "r"(c1), "h"((uint16_t)3) : "memory");
}
__device__ __forceinline__ void bulk_g2s(uint32_t dst, const void* src, int bytes, uint32_t bar) {
  asm volatile("cp.async.bulk.shared::cluster.global.mbarrier::complete_tx::bytes [%0], [%1], %2, [%3];" ::"r"(dst), "l"(src), "r"(bytes), "r"(bar) : "memory");
}
__device__ __forceinline__ void bulk_s2g(void* dst, uint32_t src, int bytes) {
  asm volatile("cp.async.bulk.global.shared::cta.bulk_group [%0], [%1], %2;" ::"l"(dst), "r"(src), "r"(bytes) : "memory");
}
__device__ __forceinline__ void bulk_s2s(uint32_t dst, uint32_t src, int bytes, uint32_t bar) {
  asm volatile("cp.async.bulk.shared::cluster.shared::cta.mbarrier::complete_tx::bytes [%0], [%1], %2, [%3];" ::"r"(dst), "r"(src), "r"(bytes), "r"(bar) : "memory");
}
__device__ __forceinline__ void bulk_commit() { asm volatile("cp.async.bulk.commit_group;" ::: "memory"); }
__device__ __forceinline__ void bulk_wait0() { asm volatile("cp.async.bulk.wait_group 0;" ::: "memory"); }
__device__ __forceinline__ void bulk_wait0_read() { asm volatile("cp.async.bulk.wait_group.read 0;" ::: "memory"); }
__device__ __forceinline__ void prefetch_map(const CUtensorMap* m) { asm volatile("prefetch.tensormap [%0];" ::"l"(m) : "memory"); }

__device__ __forceinline__ void ldsm4(uint32_t* r, uint32_t a) { asm volatile("ldmatrix.sync.aligned.m8n8.x4.shared.b16 {%0,%1,%2,%3}, [%4];" : "=r"(r[0]), "=r"(r[1]), "=r"(r[2]), "=r"(r[3]) : "r"(a) : "memory"); }
__device__ __forceinline__ void stsm4(uint32_t a, uint32_t r0, uint32_t r1, uint32_t r2, uint32_t r3) { asm volatile("stmatrix.sync.aligned.m8n8.x4.shared.b16 [%0], {%1,%2,%3,%4};" ::"r"(a), "r"(r0), "r"(r1), "r"(r2), "r"(r3) : "memory"); }
__device__ __forceinline__ void stsm2(uint32_t a, uint32_t r0, uint32_t r1) { asm volatile("stmatrix.sync.aligned.m8n8.x2.shared.b16 [%0], {%1,%2};" ::"r"(a), "r"(r0), "r"(r1) : "memory"); }
__device__ __forceinline__ uint32_t pack2(float lo, float hi) { uint32_t r; asm("cvt.rn.bf16x2.f32 %0, %1, %2;" : "=r"(r) : "f"(hi), "f"(lo)); return r; }
__device__ __forceinline__ float bf_lo(uint32_t v) { return __uint_as_float(v << 16); }
__device__ __forceinline__ float bf_hi(uint32_t v) { return __uint_as_float(v & 0xffff0000u); }
__device__ __forceinline__ float rbf(float v) { return bf_lo(pack2(v, 0.f)); }
__device__ __forceinline__ uint32_t sub2(uint32_t a, uint32_t b) { uint32_t r; asm("sub.rn.bf16x2 %0, %1, %2;" : "=r"(r) : "r"(a), "r"(b)); return r; }
__device__ __forceinline__ float ex2(float v) { float r; asm("ex2.approx.ftz.f32 %0, %1;" : "=f"(r) : "f"(v)); return r; }
__device__ __forceinline__ float rcp(float v) { float r; asm("rcp.approx.ftz.f32 %0, %1;" : "=f"(r) : "f"(v)); return r; }
__device__ __forceinline__ uint4 lds128(uint32_t a) { uint4 v; asm volatile("ld.shared.v4.u32 {%0,%1,%2,%3}, [%4];" : "=r"(v.x), "=r"(v.y), "=r"(v.z), "=r"(v.w) : "r"(a) : "memory"); return v; }
__device__ __forceinline__ void sts128(uint32_t a, uint4 v) { asm volatile("st.shared.v4.u32 [%0], {%1,%2,%3,%4};" ::"r"(a), "r"(v.x), "r"(v.y), "r"(v.z), "r"(v.w) : "memory"); }
__device__ __forceinline__ uint4 ldg128(const void* p) { uint4 v; asm volatile("ld.global.nc.L1::no_allocate.v4.u32 {%0,%1,%2,%3}, [%4];" : "=r"(v.x), "=r"(v.y), "=r"(v.z), "=r"(v.w) : "l"(p)); return v; }

__device__ __forceinline__ void wg_fence() { asm volatile("wgmma.fence.sync.aligned;" ::: "memory"); }
__device__ __forceinline__ void wg_commit() { asm volatile("wgmma.commit_group.sync.aligned;" ::: "memory"); }
template <int N> __device__ __forceinline__ void wg_wait() { asm volatile("wgmma.wait_group.sync.aligned %0;" ::"n"(N) : "memory"); }
template <int N> __device__ __forceinline__ void reg_fence(float* d) {
#pragma unroll
  for (int i = 0; i < N; i++) asm volatile("" : "+f"(d[i])::"memory");
}
template <int N> __device__ __forceinline__ void zero(float* d) {
#pragma unroll
  for (int i = 0; i < N; i++) d[i] = 0.f;
}
__device__ __forceinline__ uint64_t mkdesc(uint32_t addr, uint32_t lbo, uint32_t sbo, uint32_t sw) {
  return (uint64_t)((addr & 0x3FFFF) >> 4) | ((uint64_t)(lbo >> 4) << 16) | ((uint64_t)(sbo >> 4) << 32) | ((uint64_t)sw << 62);
}

__device__ __forceinline__ void wgmma_rs_n56(float* d, const uint32_t* a, uint64_t db, int sd) {
  asm volatile("{\n.reg .pred p;\nsetp.ne.b32 p, %33, 0;\nwgmma.mma_async.sync.aligned.m64n56k16.f32.bf16.bf16 {%0,%1,%2,%3,%4,%5,%6,%7,%8,%9,%10,%11,%12,%13,%14,%15,%16,%17,%18,%19,%20,%21,%22,%23,%24,%25,%26,%27}, {%28,%29,%30,%31}, %32, p, 1, 1, 1;\n}\n"
    : "+f"(d[0]),"+f"(d[1]),"+f"(d[2]),"+f"(d[3]),"+f"(d[4]),"+f"(d[5]),"+f"(d[6]),"+f"(d[7]),"+f"(d[8]),"+f"(d[9]),"+f"(d[10]),"+f"(d[11]),"+f"(d[12]),"+f"(d[13]),"+f"(d[14]),"+f"(d[15]),"+f"(d[16]),"+f"(d[17]),"+f"(d[18]),"+f"(d[19]),"+f"(d[20]),"+f"(d[21]),"+f"(d[22]),"+f"(d[23]),"+f"(d[24]),"+f"(d[25]),"+f"(d[26]),"+f"(d[27])
    : "r"(a[0]),"r"(a[1]),"r"(a[2]),"r"(a[3]),"l"(db),"r"(sd));
}
__device__ __forceinline__ void wgmma_rs_n64(float* d, const uint32_t* a, uint64_t db, int sd) {
  asm volatile("{\n.reg .pred p;\nsetp.ne.b32 p, %37, 0;\nwgmma.mma_async.sync.aligned.m64n64k16.f32.bf16.bf16 {%0,%1,%2,%3,%4,%5,%6,%7,%8,%9,%10,%11,%12,%13,%14,%15,%16,%17,%18,%19,%20,%21,%22,%23,%24,%25,%26,%27,%28,%29,%30,%31}, {%32,%33,%34,%35}, %36, p, 1, 1, 1;\n}\n"
    : "+f"(d[0]),"+f"(d[1]),"+f"(d[2]),"+f"(d[3]),"+f"(d[4]),"+f"(d[5]),"+f"(d[6]),"+f"(d[7]),"+f"(d[8]),"+f"(d[9]),"+f"(d[10]),"+f"(d[11]),"+f"(d[12]),"+f"(d[13]),"+f"(d[14]),"+f"(d[15]),"+f"(d[16]),"+f"(d[17]),"+f"(d[18]),"+f"(d[19]),"+f"(d[20]),"+f"(d[21]),"+f"(d[22]),"+f"(d[23]),"+f"(d[24]),"+f"(d[25]),"+f"(d[26]),"+f"(d[27]),"+f"(d[28]),"+f"(d[29]),"+f"(d[30]),"+f"(d[31])
    : "r"(a[0]),"r"(a[1]),"r"(a[2]),"r"(a[3]),"l"(db),"r"(sd));
}
__device__ __forceinline__ void wgmma_rs_n128(float* d, const uint32_t* a, uint64_t db, int sd) {
  asm volatile("{\n.reg .pred p;\nsetp.ne.b32 p, %69, 0;\nwgmma.mma_async.sync.aligned.m64n128k16.f32.bf16.bf16 {%0,%1,%2,%3,%4,%5,%6,%7,%8,%9,%10,%11,%12,%13,%14,%15,%16,%17,%18,%19,%20,%21,%22,%23,%24,%25,%26,%27,%28,%29,%30,%31,%32,%33,%34,%35,%36,%37,%38,%39,%40,%41,%42,%43,%44,%45,%46,%47,%48,%49,%50,%51,%52,%53,%54,%55,%56,%57,%58,%59,%60,%61,%62,%63}, {%64,%65,%66,%67}, %68, p, 1, 1, 1;\n}\n"
    : "+f"(d[0]),"+f"(d[1]),"+f"(d[2]),"+f"(d[3]),"+f"(d[4]),"+f"(d[5]),"+f"(d[6]),"+f"(d[7]),"+f"(d[8]),"+f"(d[9]),"+f"(d[10]),"+f"(d[11]),"+f"(d[12]),"+f"(d[13]),"+f"(d[14]),"+f"(d[15]),"+f"(d[16]),"+f"(d[17]),"+f"(d[18]),"+f"(d[19]),"+f"(d[20]),"+f"(d[21]),"+f"(d[22]),"+f"(d[23]),"+f"(d[24]),"+f"(d[25]),"+f"(d[26]),"+f"(d[27]),"+f"(d[28]),"+f"(d[29]),"+f"(d[30]),"+f"(d[31]),"+f"(d[32]),"+f"(d[33]),"+f"(d[34]),"+f"(d[35]),"+f"(d[36]),"+f"(d[37]),"+f"(d[38]),"+f"(d[39]),"+f"(d[40]),"+f"(d[41]),"+f"(d[42]),"+f"(d[43]),"+f"(d[44]),"+f"(d[45]),"+f"(d[46]),"+f"(d[47]),"+f"(d[48]),"+f"(d[49]),"+f"(d[50]),"+f"(d[51]),"+f"(d[52]),"+f"(d[53]),"+f"(d[54]),"+f"(d[55]),"+f"(d[56]),"+f"(d[57]),"+f"(d[58]),"+f"(d[59]),"+f"(d[60]),"+f"(d[61]),"+f"(d[62]),"+f"(d[63])
    : "r"(a[0]),"r"(a[1]),"r"(a[2]),"r"(a[3]),"l"(db),"r"(sd));
}
__device__ __forceinline__ void wgmma_ss_n112(float* d, uint64_t da, uint64_t db, int sd) {
  asm volatile("{\n.reg .pred p;\nsetp.ne.b32 p, %58, 0;\nwgmma.mma_async.sync.aligned.m64n112k16.f32.bf16.bf16 {%0,%1,%2,%3,%4,%5,%6,%7,%8,%9,%10,%11,%12,%13,%14,%15,%16,%17,%18,%19,%20,%21,%22,%23,%24,%25,%26,%27,%28,%29,%30,%31,%32,%33,%34,%35,%36,%37,%38,%39,%40,%41,%42,%43,%44,%45,%46,%47,%48,%49,%50,%51,%52,%53,%54,%55}, %56, %57, p, 1, 1, 0, 1;\n}\n"
    : "+f"(d[0]),"+f"(d[1]),"+f"(d[2]),"+f"(d[3]),"+f"(d[4]),"+f"(d[5]),"+f"(d[6]),"+f"(d[7]),"+f"(d[8]),"+f"(d[9]),"+f"(d[10]),"+f"(d[11]),"+f"(d[12]),"+f"(d[13]),"+f"(d[14]),"+f"(d[15]),"+f"(d[16]),"+f"(d[17]),"+f"(d[18]),"+f"(d[19]),"+f"(d[20]),"+f"(d[21]),"+f"(d[22]),"+f"(d[23]),"+f"(d[24]),"+f"(d[25]),"+f"(d[26]),"+f"(d[27]),"+f"(d[28]),"+f"(d[29]),"+f"(d[30]),"+f"(d[31]),"+f"(d[32]),"+f"(d[33]),"+f"(d[34]),"+f"(d[35]),"+f"(d[36]),"+f"(d[37]),"+f"(d[38]),"+f"(d[39]),"+f"(d[40]),"+f"(d[41]),"+f"(d[42]),"+f"(d[43]),"+f"(d[44]),"+f"(d[45]),"+f"(d[46]),"+f"(d[47]),"+f"(d[48]),"+f"(d[49]),"+f"(d[50]),"+f"(d[51]),"+f"(d[52]),"+f"(d[53]),"+f"(d[54]),"+f"(d[55])
    : "l"(da),"l"(db),"r"(sd));
}
__device__ __forceinline__ void wgmma_ss_n56(float* d, uint64_t da, uint64_t db, int sd) {
  asm volatile("{\n.reg .pred p;\nsetp.ne.b32 p, %30, 0;\nwgmma.mma_async.sync.aligned.m64n56k16.f32.bf16.bf16 {%0,%1,%2,%3,%4,%5,%6,%7,%8,%9,%10,%11,%12,%13,%14,%15,%16,%17,%18,%19,%20,%21,%22,%23,%24,%25,%26,%27}, %28, %29, p, 1, 1, 0, 1;\n}\n"
    : "+f"(d[0]),"+f"(d[1]),"+f"(d[2]),"+f"(d[3]),"+f"(d[4]),"+f"(d[5]),"+f"(d[6]),"+f"(d[7]),"+f"(d[8]),"+f"(d[9]),"+f"(d[10]),"+f"(d[11]),"+f"(d[12]),"+f"(d[13]),"+f"(d[14]),"+f"(d[15]),"+f"(d[16]),"+f"(d[17]),"+f"(d[18]),"+f"(d[19]),"+f"(d[20]),"+f"(d[21]),"+f"(d[22]),"+f"(d[23]),"+f"(d[24]),"+f"(d[25]),"+f"(d[26]),"+f"(d[27])
    : "l"(da),"l"(db),"r"(sd));
}
__device__ __forceinline__ void wgmma_ssk_n80(float* d, uint64_t da, uint64_t db, int sd) {
  asm volatile("{\n.reg .pred p;\nsetp.ne.b32 p, %42, 0;\nwgmma.mma_async.sync.aligned.m64n80k16.f32.bf16.bf16 {%0,%1,%2,%3,%4,%5,%6,%7,%8,%9,%10,%11,%12,%13,%14,%15,%16,%17,%18,%19,%20,%21,%22,%23,%24,%25,%26,%27,%28,%29,%30,%31,%32,%33,%34,%35,%36,%37,%38,%39}, %40, %41, p, 1, 1, 0, 0;\n}\n"
    : "+f"(d[0]),"+f"(d[1]),"+f"(d[2]),"+f"(d[3]),"+f"(d[4]),"+f"(d[5]),"+f"(d[6]),"+f"(d[7]),"+f"(d[8]),"+f"(d[9]),"+f"(d[10]),"+f"(d[11]),"+f"(d[12]),"+f"(d[13]),"+f"(d[14]),"+f"(d[15]),"+f"(d[16]),"+f"(d[17]),"+f"(d[18]),"+f"(d[19]),"+f"(d[20]),"+f"(d[21]),"+f"(d[22]),"+f"(d[23]),"+f"(d[24]),"+f"(d[25]),"+f"(d[26]),"+f"(d[27]),"+f"(d[28]),"+f"(d[29]),"+f"(d[30]),"+f"(d[31]),"+f"(d[32]),"+f"(d[33]),"+f"(d[34]),"+f"(d[35]),"+f"(d[36]),"+f"(d[37]),"+f"(d[38]),"+f"(d[39])
    : "l"(da),"l"(db),"r"(sd));
}
__device__ __forceinline__ void wgmma_rs_n32(float* d, const uint32_t* a, uint64_t db, int sd) {
  asm volatile("{\n.reg .pred p;\nsetp.ne.b32 p, %21, 0;\nwgmma.mma_async.sync.aligned.m64n32k16.f32.bf16.bf16 {%0,%1,%2,%3,%4,%5,%6,%7,%8,%9,%10,%11,%12,%13,%14,%15}, {%16,%17,%18,%19}, %20, p, 1, 1, 1;\n}\n"
    : "+f"(d[0]),"+f"(d[1]),"+f"(d[2]),"+f"(d[3]),"+f"(d[4]),"+f"(d[5]),"+f"(d[6]),"+f"(d[7]),"+f"(d[8]),"+f"(d[9]),"+f"(d[10]),"+f"(d[11]),"+f"(d[12]),"+f"(d[13]),"+f"(d[14]),"+f"(d[15])
    : "r"(a[0]),"r"(a[1]),"r"(a[2]),"r"(a[3]),"l"(db),"r"(sd));
}

constexpr float LOG2E = 1.4426950408889634f;

__device__ __forceinline__ float swiglu(float g, float u, float c1, float r2) {
  float e = ex2(g * c1);
  return (g * u) * (r2 * rcp(1.f + e));
}

struct Ring {
  uint32_t st, ph;
  __device__ __forceinline__ void next() { if (++st == NST) { st = 0; ph ^= 1; } }
};

__global__ void __cluster_dims__(2, 1, 1) __launch_bounds__(512, 1) fused_kernel(const __grid_constant__ Params p) {
  extern __shared__ __align__(1024) uint8_t smem[];
  const uint32_t sb = s2u(smem);
  const uint32_t bars = sb + OFF_BAR;
  const int tid = threadIdx.x, warp = __shfl_sync(~0u, tid >> 5, 0), lane = tid & 31;
  const int rank = blockIdx.x & 1, cid = blockIdx.x >> 1;
  int grp, j;
  if (cid < 4) { grp = 0; j = 4 + cid; }
  else if (cid < 36) { grp = (cid - 4) & 7; j = (cid - 4) >> 3; }
  else { j = ((cid - 36) * 37) >> 8; grp = 1 + (cid - 36) - 7 * j; j += 4; }
  const int tb = 2 * grp + rank;
  const int T2 = 2 * grp + (j >> 2);
  const int qn = j & 3;
#define BAR(i) (bars + 8 * (i))

  if (warp < 8) {
    if (tid == 0) { TG(0); TS(1); }
    const int wg = warp >> 2;
    const int g = lane >> 2, q = lane & 3;
    asm volatile("barrier.cluster.arrive.relaxed.aligned;" ::: "memory");
    if (wg == 1) asm volatile("barrier.cluster.wait.acquire.aligned;" ::: "memory");
    const uint32_t xs = sb + (wg == 0 ? OFF_K : 7 * STAGE);
    if (lane == 0) {
      const int w = warp & 3;
      const uint32_t b0 = BAR(B_X + wg * 7 + w);
      mbar_init(b0, 1);
      if (w < 3) mbar_init(b0 + 32, 1);
      fence_async_smem();
      mbar_expect(b0, 8192);
      tma2d(xs + w * 8192, &p.xm, b0, w * 64, tb * 128 + wg * 64);
      if (w < 3) {
        mbar_expect(b0 + 32, 8192);
        tma2d(xs + (w + 4) * 8192 + (warp == 6 ? 57344 : 0), &p.xm, b0 + 32, (w + 4) * 64, tb * 128 + wg * 64);
      }
    }
    TSW(2 + wg);
    asm volatile("setmaxnreg.inc.sync.aligned.u32 208;");
    if (wg == 0) { asm volatile("bar.sync 4, 128;" ::: "memory"); asm volatile("barrier.cluster.wait.acquire.aligned;" ::: "memory"); }
    else asm volatile("bar.sync 6, 128;" ::: "memory");

    uint32_t a[112];
    float dm0, dm1;
    {
      const uint32_t xa = xs + ((warp & 3) * 16 + (lane & 15)) * 128;
      float s0a = 0.f, s0b = 0.f, s1a = 0.f, s1b = 0.f;
#pragma unroll
      for (int kt = 0; kt < 7; kt++) {
        mbar_wait(BAR(B_X + wg * 7 + kt), 0);
        const uint32_t xk = xa + kt * 8192 + ((kt == 6 && wg == 1) ? 57344 : 0);
#pragma unroll
        for (int ks = 0; ks < 4; ks++) ldsm4(&a[16 * kt + 4 * ks], xk + (((2 * ks + (lane >> 4)) ^ (lane & 7)) << 4));
#pragma unroll
        for (int ks = 0; ks < 4; ks++) {
          const uint32_t* u = &a[16 * kt + 4 * ks];
          s0a += bf_lo(u[0]) + bf_hi(u[0]); s1a += bf_lo(u[1]) + bf_hi(u[1]);
          s0b += bf_lo(u[2]) + bf_hi(u[2]); s1b += bf_lo(u[3]) + bf_hi(u[3]);
        }
        asm volatile("" : "+f"(s0a), "+f"(s0b), "+f"(s1a), "+f"(s1b));
      }
      __syncwarp();
      if (lane == 0) { mbar_arrive(BAR(B_XFREE)); mbar_arrive_cluster(mapa(BAR(B_XFREE), rank ^ 1)); }
      float s0 = s0a + s0b, s1 = s1a + s1b;
      s0 += __shfl_xor_sync(~0u, s0, 1); s1 += __shfl_xor_sync(~0u, s1, 1);
      s0 += __shfl_xor_sync(~0u, s0, 2); s1 += __shfl_xor_sync(~0u, s1, 2);
      TSW(4 + wg);
      const float mu0 = s0 * (1.f / D_), mu1 = s1 * (1.f / D_);
      const uint32_t m0 = pack2(mu0, mu0), m1 = pack2(mu1, mu1);
      dm0 = mu0 - bf_lo(m0); dm1 = mu1 - bf_lo(m1);
#pragma unroll
      for (int i = 0; i < 112; i++) a[i] = sub2(a[i], (i & 1) ? m1 : m0);
    }
    const bool rel = (lane == 0) && ((warp & 3) < 2);
    uint32_t rel_base = mapa(bars, rank ^ (warp & 1)) + 8 * B_EMPTY;
    TSW(6 + wg);

    Ring rg{0, 0};
    const uint64_t dB128 = mkdesc(sb, 8192, 1024, 1);
    float rs0, rs1;

    {
      float ss0 = 0.f, ss1 = 0.f;
      float accK[28], accV[28];
      zero<28>(accK); zero<28>(accV);
      if (wg == 1) asm volatile("bar.sync 1, 256;" ::: "memory");
      const uint64_t dW = dB128 + (j & 1);
      uint32_t prev = 0;
#pragma unroll
      for (int kt = 0; kt < 7; kt++) {
        mbar_wait(BAR(B_FULL + rg.st), rg.ph);
        if (kt == 0) TSW(8 + wg);
        const uint64_t db = dW + (uint64_t)(rg.st * (STAGE >> 4));
        wg_fence();
#pragma unroll
        for (int ks = 0; ks < 4; ks++) {
          wgmma_rs_n56(accK, &a[(kt * 4 + ks) * 4], db + ks * 128, kt | ks);
          wgmma_rs_n56(accV, &a[(kt * 4 + ks) * 4], db + 512 + ks * 128, kt | ks);
        }
        wg_commit();
        if (kt == LAG0 && wg == 0) asm volatile("bar.arrive 1, 256;" ::: "memory");
        if (kt == LAGB && wg == 1) asm volatile("bar.arrive 5, 256;" ::: "memory");
        if (kt > 0) {
          wg_wait<1>();
          if (rel) mbar_arrive_cluster(rel_base + 8 * prev);
#pragma unroll
          for (int i = (kt - 1) * 16; i < kt * 16; i++) {
            asm volatile("" : "+r"(a[i]));
            const float lo = bf_lo(a[i]), hi = bf_hi(a[i]);
            if (i & 1) { ss1 = fmaf(lo, lo, ss1); ss1 = fmaf(hi, hi, ss1); } else { ss0 = fmaf(lo, lo, ss0); ss0 = fmaf(hi, hi, ss0); }
          }
          asm volatile("" : "+f"(ss0), "+f"(ss1));
        }
        prev = rg.st; rg.next();
      }
      wg_wait<0>();
      reg_fence<28>(accK); reg_fence<28>(accV);
      if (rel) mbar_arrive_cluster(rel_base + 8 * prev);
      TSW(10 + wg);
#pragma unroll
      for (int i = 96; i < 112; i++) {
        asm volatile("" : "+r"(a[i]));
        const float lo = bf_lo(a[i]), hi = bf_hi(a[i]);
        if (i & 1) { ss1 = fmaf(lo, lo, ss1); ss1 = fmaf(hi, hi, ss1); } else { ss0 = fmaf(lo, lo, ss0); ss0 = fmaf(hi, hi, ss0); }
      }
      ss0 += __shfl_xor_sync(~0u, ss0, 1); ss1 += __shfl_xor_sync(~0u, ss1, 1);
      ss0 += __shfl_xor_sync(~0u, ss0, 2); ss1 += __shfl_xor_sync(~0u, ss1, 2);
      const float v0 = fmaxf(ss0 * (1.f / D_) - dm0 * dm0, 0.f), v1 = fmaxf(ss1 * (1.f / D_) - dm1 * dm1, 0.f);
      rs0 = 1.f / rbf(sqrtf(rbf(rbf(v0) + 1e-5f)));
      rs1 = 1.f / rbf(sqrtf(rbf(rbf(v1) + 1e-5f)));
      mbar_wait(BAR(B_XFREE), 0);
      const uint32_t ka = sb + OFF_K + (lane >> 4) * KVB + (2 + 2 * warp + ((lane >> 3) & 1)) * 896 + (lane & 7) * 16;
#pragma unroll
      for (int c = 0; c < 7; c++)
        stsm4(ka + c * 128, pack2(accK[4 * c] * rs0, accK[4 * c + 1] * rs0), pack2(accK[4 * c + 2] * rs1, accK[4 * c + 3] * rs1),
              pack2(accV[4 * c] * rs0, accV[4 * c + 1] * rs0), pack2(accV[4 * c + 2] * rs1, accV[4 * c + 3] * rs1));
      fence_async_smem();
      __syncwarp();
      if (lane == 0) mbar_arrive(BAR(B_KV));
      TSW(12 + wg);
    }
    const float c10 = -rs0 * LOG2E, c11 = -rs1 * LOG2E, r20 = rs0 * rs0, r21 = rs1 * rs1;
    const uint32_t tile_off = (lane >> 4) * 1024 + ((warp & 3) * 16 + (lane & 15)) * 16;
    const uint32_t hs_st = sb + OFF_HS + wg * 8192 + tile_off;

    {
      const uint64_t dB64 = mkdesc(sb + 8192, 4096, 512, 2);
      float accQ[28], accG[32];
      zero<28>(accQ); zero<32>(accG);
      if (wg == 1) asm volatile("bar.sync 1, 256;" ::: "memory"); else asm volatile("bar.sync 5, 256;" ::: "memory");
      const uint64_t dW = dB128 + (j & 1);
      uint32_t prev = 0;
#pragma unroll
      for (int kt = 0; kt < 7; kt++) {
        mbar_wait(BAR(B_FULL + rg.st), rg.ph);
        if (kt == 0) TSW(14 + wg);
        const uint64_t so = (uint64_t)(rg.st * (STAGE >> 4));
        wg_fence();
#pragma unroll
        for (int ks = 0; ks < 4; ks++) {
          wgmma_rs_n56(accQ, &a[(kt * 4 + ks) * 4], dW + so + ks * 128, kt | ks);
          wgmma_rs_n64(accG, &a[(kt * 4 + ks) * 4], dB64 + so + ks * 64, kt | ks);
        }
        wg_commit();
        if (kt == LAGA && wg == 0) asm volatile("bar.arrive 1, 256;" ::: "memory");
        if (kt == LAGB && wg == 1) asm volatile("bar.arrive 5, 256;" ::: "memory");
        if (kt > 0) { wg_wait<1>(); if (rel) mbar_arrive_cluster(rel_base + 8 * prev); }
        prev = rg.st; rg.next();
      }
      wg_wait<0>();
      reg_fence<28>(accQ); reg_fence<32>(accG);
      if (rel) mbar_arrive_cluster(rel_base + 8 * prev);
      TSW(16 + wg);
      const uint32_t qa = sb + OFF_Q + wg * 8192 + tile_off;
      uint32_t qp[14];
#pragma unroll
      for (int c = 0; c < 7; c++) { qp[2 * c] = pack2(accQ[4 * c] * rs0, accQ[4 * c + 1] * rs0); qp[2 * c + 1] = pack2(accQ[4 * c + 2] * rs1, accQ[4 * c + 3] * rs1); }
      stsm4(qa, qp[0], qp[1], qp[2], qp[3]);
      stsm4(qa + 2048, qp[4], qp[5], q < 2 ? qp[6] : 0u, q < 2 ? qp[7] : 0u);
      stsm4(qa + 4096, q < 2 ? 0u : qp[6], q < 2 ? 0u : qp[7], qp[8], qp[9]);
      stsm4(qa + 6144, qp[10], qp[11], qp[12], qp[13]);
      fence_async_smem();
      __syncwarp();
      if (lane == 0) mbar_arrive(BAR(B_Q + wg));
#pragma unroll
      for (int c = 0; c < 2; c++) {
        uint32_t hp[4];
#pragma unroll
        for (int e = 0; e < 2; e++) {
          const float* gg = &accG[8 * c + 4 * e]; const float* uu = &accG[16 + 8 * c + 4 * e];
          hp[2 * e] = pack2(swiglu(gg[0], uu[0], c10, r20), swiglu(gg[1], uu[1], c10, r20));
          hp[2 * e + 1] = pack2(swiglu(gg[2], uu[2], c11, r21), swiglu(gg[3], uu[3], c11, r21));
        }
        stsm4(hs_st + c * 2048, hp[0], hp[1], hp[2], hp[3]);
      }
      fence_async_smem();
      __syncwarp();
      if (lane == 0) mbar_arrive(BAR(B_H + wg));
      TSW(18 + wg);
    }

#pragma unroll 1
    for (int c3 = 0; c3 < 3; c3++) {
      float acc[64];
      zero<64>(acc);
      if (c3 == 2) rel_base = mapa(bars, rank) + 8 * B_EMPTY;
      if (wg == 1) asm volatile("bar.sync 1, 256;" ::: "memory"); else asm volatile("bar.sync 5, 256;" ::: "memory");
      const int lag = wg == 0 ? LAGA : (c3 == 2 ? LAGD : LAGB);
      uint32_t prev = 0;
#pragma unroll
      for (int kt = 0; kt < 7; kt++) {
        mbar_wait(BAR(B_FULL + rg.st), rg.ph);
        if (c3 == 1) TSW(70 + 2 * kt + wg);
        if (kt == 0) TSW(20 + 6 * c3 + wg);
        const uint64_t db = dB128 + (uint64_t)(rg.st * (STAGE >> 4));
        wg_fence();
#pragma unroll
        for (int ks = 0; ks < 4; ks++) wgmma_rs_n128(acc, &a[(kt * 4 + ks) * 4], db + ks * 128, kt | ks);
        wg_commit();
        if (kt == lag) asm volatile("bar.arrive %0, 256;" ::"r"(1 + 4 * wg) : "memory");
        if (kt > 0) { wg_wait<1>(); if (rel) mbar_arrive_cluster(rel_base + 8 * prev); }
        prev = rg.st; rg.next();
      }
      wg_wait<0>();
      reg_fence<64>(acc);
      if (rel) mbar_arrive_cluster(rel_base + 8 * prev);
      TSW(22 + 6 * c3 + wg);
      mbar_wait(BAR(B_HFREE + wg), c3 & 1);
#pragma unroll
      for (int c = 0; c < 4; c++) {
        uint32_t hp[4];
#pragma unroll
        for (int e = 0; e < 2; e++) {
          const float* gg = &acc[8 * c + 4 * e]; const float* uu = &acc[32 + 8 * c + 4 * e];
          hp[2 * e] = pack2(swiglu(gg[0], uu[0], c10, r20), swiglu(gg[1], uu[1], c10, r20));
          hp[2 * e + 1] = pack2(swiglu(gg[2], uu[2], c11, r21), swiglu(gg[3], uu[3], c11, r21));
        }
        stsm4(hs_st + c * 2048, hp[0], hp[1], hp[2], hp[3]);
      }
      fence_async_smem();
      __syncwarp();
      if (lane == 0) mbar_arrive(BAR(B_H + wg));
      TSW(24 + 6 * c3 + wg);
    }

    const int ocol = qn * 112 + rank * 56;
    uint32_t xr[14];
    {
      const __nv_bfloat16* xp = p.x + (size_t)(T2 * 128 + warp * 16 + g) * D_ + ocol + 2 * q;
#pragma unroll
      for (int c = 0; c < 7; c++) {
        xr[2 * c] = __ldg(reinterpret_cast<const uint32_t*>(xp + 8 * c));
        xr[2 * c + 1] = __ldg(reinterpret_cast<const uint32_t*>(xp + 8 * D_ + 8 * c));
      }
    }
    const uint64_t dA = mkdesc(sb + wg * 8192, 1024, 128, 0);
    const uint64_t dBn = mkdesc(sb, 128, 1024, 0);
    float acc[56];
    zero<56>(acc);
    if (wg == 0) asm volatile("bar.sync 5, 256;" ::: "memory");
    {
      uint32_t prevA = 0, prevB = 0;
#pragma unroll 1
      for (int kt = 0; kt < 14; kt++) {
        const uint32_t sa = rg.st; mbar_wait(BAR(B_FULL + rg.st), rg.ph); rg.next();
        const uint32_t sB = rg.st; mbar_wait(BAR(B_FULL + rg.st), rg.ph); rg.next();
        TSW(84 + 2 * kt + wg);
        const uint64_t da = dA + (uint64_t)(sa * (STAGE >> 4)), db = dBn + (uint64_t)(sB * (STAGE >> 4));
        wg_fence();
#pragma unroll
        for (int ks = 0; ks < 4; ks++) wgmma_ss_n112(acc, da + ks * 128, db + ks * 16, kt | ks);
        wg_commit();
        if (kt > 0) { wg_wait<1>(); if (rel) { mbar_arrive_cluster(rel_base + 8 * prevA); mbar_arrive_cluster(rel_base + 8 * prevB); } }
        prevA = sa; prevB = sB;
      }
      wg_wait<0>();
      reg_fence<56>(acc);
      if (rel) { mbar_arrive_cluster(rel_base + 8 * prevA); mbar_arrive_cluster(rel_base + 8 * prevB); }
      TSW(38 + wg);
    }
    float fk[28];
    {
      mbar_wait(BAR(B_KVFREE), 0);
      const uint32_t dst = mapa(sb + OFF_PART + wg * 14336 + (tid & 127) * 16, rank ^ 1);
      const uint32_t pb = mapa(BAR(B_PART + wg), rank ^ 1);
#pragma unroll
      for (int i = 0; i < 7; i++) {
        float v[4];
#pragma unroll
        for (int e = 0; e < 4; e++) {
          v[e] = rank ? acc[4 * i + e] : acc[28 + 4 * i + e];
          fk[4 * i + e] = rank ? acc[28 + 4 * i + e] : acc[4 * i + e];
        }
        asm volatile("st.async.shared::cluster.mbarrier::complete_tx::bytes.v4.f32 [%0], {%1,%2,%3,%4}, [%5];"
                     ::"r"(dst + i * 2048), "f"(v[0]), "f"(v[1]), "f"(v[2]), "f"(v[3]), "r"(pb) : "memory");
      }
    }
    TSW(40 + wg);
    float sacc[28];
    zero<28>(sacc);
    {
      uint32_t sB = 0;
#pragma unroll 1
      for (int kt = 0; kt < 7; kt++) {
        if ((kt & 1) == 0) { sB = rg.st; mbar_wait(BAR(B_FULL + rg.st), rg.ph); rg.next(); }
        const uint32_t sa = rg.st; mbar_wait(BAR(B_FULL + rg.st), rg.ph); rg.next();
        TSW(112 + 2 * kt + wg);
        const uint64_t da = dA + (uint64_t)(sa * (STAGE >> 4)), db = dBn + (uint64_t)(sB * (STAGE >> 4) + (kt & 1) * 448);
        wg_fence();
#pragma unroll
        for (int ks = 0; ks < 4; ks++) wgmma_ss_n56(sacc, da + ks * 128, db + ks * 16, kt | ks);
        wg_commit();
        if (kt == 2) { wg_wait<1>(); if (rel) mbar_arrive_cluster(rel_base + 8 * (63 % NST)); }
      }
    }
    {
      mbar_wait(BAR(B_PART + wg), 0);
      const uint32_t src = sb + OFF_PART + wg * 14336 + (tid & 127) * 16;
#pragma unroll
      for (int c = 0; c < 7; c++) {
        const uint4 pv = lds128(src + c * 2048);
        const float f[4] = {fk[4 * c] + __uint_as_float(pv.x), fk[4 * c + 1] + __uint_as_float(pv.y),
                            fk[4 * c + 2] + __uint_as_float(pv.z), fk[4 * c + 3] + __uint_as_float(pv.w)};
#pragma unroll
        for (int e = 0; e < 4; e++) {
          const float fb = rbf(f[e]);
          fk[4 * c + e] = rbf(fb * rcp(1.f + ex2(-LOG2E * fb)));
        }
      }
      reg_fence<28>(fk);
      mbar_wait(BAR(B_HFREE + wg), 1);
      wg_wait<0>();
      reg_fence<28>(sacc);
      TSW(42 + wg);
      const uint32_t ot = sb + OFF_HS + warp * 2048;
      uint32_t yo[14];
#pragma unroll
      for (int c = 0; c < 14; c++) {
        const uint32_t sp = pack2(sacc[2 * c], sacc[2 * c + 1]);
        const uint32_t y = pack2(bf_lo(sp) * fk[2 * c], bf_hi(sp) * fk[2 * c + 1]);
        yo[c] = pack2(bf_lo(xr[c]) + bf_lo(y), bf_hi(xr[c]) + bf_hi(y));
      }
      const uint32_t oa = ot + (lane & 15) * 112 + (lane >> 4) * 16;
#pragma unroll
      for (int c = 0; c < 3; c++) stsm4(oa + c * 32, yo[4 * c], yo[4 * c + 1], yo[4 * c + 2], yo[4 * c + 3]);
      stsm2(oa + 96, yo[12], yo[13]);
      fence_async_smem();
      __syncwarp();
      if (lane == 0) {
        asm volatile("cp.async.bulk.tensor.2d.global.shared::cta.bulk_group [%0, {%2,%3}], [%1];"
                     ::"l"(&p.outm), "r"(ot), "r"(ocol), "r"(T2 * 128 + warp * 16) : "memory");
        bulk_commit();
        bulk_wait0_read();
      }
    }
    TSW(44 + wg);
  } else if (warp < 12) {
    asm volatile("barrier.cluster.arrive.relaxed.aligned;" ::: "memory");
    asm volatile("setmaxnreg.dec.sync.aligned.u32 72;");
    asm volatile("barrier.cluster.wait.acquire.aligned;" ::: "memory");
    const int w = warp & 3, g = lane >> 2, q = lane & 3;
    const int par = g & 1;
    const float scale = 0.1889822365046136f;
    {
      mbar_wait(BAR(B_XFREE), 0);
      uint4 v[8];
#pragma unroll
      for (int pass = 0; pass < 2; pass++) {
#pragma unroll
        for (int i = 0; i < 8; i++) {
          const int k = i * 128 + (tid & 127);
          if (k < 980) {
            const int c = blockIdx.x * 980 + k, rp = c / 112, rem = c - rp * 112, ch = rem >> 1, row = 2 * rp + (rem & 1);
            if (pass == 0) v[i] = ldg128(row < F_ ? p.wd + row * 56 + ch : p.wo + (row - F_) * 56 + ch);
            else if (row < F_) { const int qq = ch / 14; g_wd[((qq * 28 + (row >> 6)) * 14 + ch - qq * 14) * 64 + (row & 63)] = v[i]; }
            else { const int e = ch / 7; g_wo[((e * 7 + ((row - F_) >> 6)) * 7 + ch - e * 7) * 64 + (row & 63)] = v[i]; }
          }
        }
      }
      asm volatile("bar.sync 2, 128;" ::: "memory");
      if (tid == 256) { flag_add_rel(g_wflag); TS(67); }
    }
    mbar_wait(BAR(B_KV), 0);
#pragma unroll 1
    for (int mt = 1; mt >= 0; mt--) {
      mbar_wait(BAR(B_Q + mt), 0);
      if (mt == 0) mbar_wait(BAR(B_HALO), 0);
      TSW(46 + 2 * mt);
      const uint32_t qa = sb + OFF_Q + mt * 8192 + (lane >> 4) * 1024 + (w * 16 + (lane & 15)) * 16;
      const uint64_t dQ = mkdesc(sb + OFF_Q + mt * 8192, 1024, 128, 0);
      const uint64_t dK = mkdesc(sb + OFF_K + mt * 7168, 128, 896, 0);
      const uint64_t dV = mkdesc(sb + OFF_V + mt * 7168, 896, 128, 0);
      const int key0 = tb * 128 + mt * 64 + w * 16 - 16;
      uint32_t o3a = 0, o3b = 0;
#pragma unroll
      for (int hh = 0; hh < 2; hh++) {
        float s[40];
        zero<40>(s);
        wg_fence();
        wgmma_ssk_n80(s, dQ + hh * 256, dK + hh * 24, 0);
        wgmma_ssk_n80(s, dQ + hh * 256 + 128, dK + hh * 24 + 16, 1);
        wg_commit();
        wg_wait<0>();
        reg_fence<40>(s);
        float l0[4], l1[4];
        float m0 = -INFINITY, m1 = -INFINITY;
#pragma unroll
        for (int n = 0; n < 4; n++) {
          float b0[4], b1[4];
#pragma unroll
          for (int ww = 0; ww < 4; ww++) {
            const float* t = &s[4 * (2 * ww + n)];
            b0[ww] = par ? t[1] : t[0]; b1[ww] = par ? t[3] : t[2];
          }
          const float r0 = (w & 2) ? ((w & 1) ? b0[3] : b0[2]) : ((w & 1) ? b0[1] : b0[0]);
          const float r1 = (w & 2) ? ((w & 1) ? b1[3] : b1[2]) : ((w & 1) ? b1[1] : b1[0]);
          const int jj = 8 * n + 2 * q + par;
          const bool tok = (key0 + jj) >= 0;
          const int d0 = g + 16 - jj, d1 = d0 + 8;
          l0[n] = (tok && d0 >= 0 && d0 <= 14) ? rbf(rbf(r0) * scale) : -INFINITY;
          l1[n] = (tok && d1 >= 0 && d1 <= 14) ? rbf(rbf(r1) * scale) : -INFINITY;
          m0 = fmaxf(m0, l0[n]); m1 = fmaxf(m1, l1[n]);
        }
        m0 = fmaxf(m0, __shfl_xor_sync(~0u, m0, 1)); m1 = fmaxf(m1, __shfl_xor_sync(~0u, m1, 1));
        m0 = fmaxf(m0, __shfl_xor_sync(~0u, m0, 2)); m1 = fmaxf(m1, __shfl_xor_sync(~0u, m1, 2));
        float z0 = 0.f, z1 = 0.f;
#pragma unroll
        for (int n = 0; n < 4; n++) {
          l0[n] = ex2((l0[n] - m0) * LOG2E); l1[n] = ex2((l1[n] - m1) * LOG2E);
          z0 += l0[n]; z1 += l1[n];
        }
        z0 += __shfl_xor_sync(~0u, z0, 1); z1 += __shfl_xor_sync(~0u, z1, 1);
        z0 += __shfl_xor_sync(~0u, z0, 2); z1 += __shfl_xor_sync(~0u, z1, 2);
        const float i0 = rcp(z0), i1 = rcp(z1);
        uint32_t pf[2][4];
#pragma unroll
        for (int n = 0; n < 4; n++) {
          const uint32_t p0 = pack2(l0[n] * i0, 0.f), p1 = pack2(l1[n] * i1, 0.f);
          pf[n >> 1][(n & 1) * 2] = p0 << (16 * par);
          pf[n >> 1][(n & 1) * 2 + 1] = p1 << (16 * par);
        }
        uint32_t pa[5][4];
#pragma unroll
        for (int k = 0; k < 5; k++)
#pragma unroll
          for (int r = 0; r < 4; r++) pa[k][r] = (k == w) ? pf[0][r] : ((k == w + 1) ? pf[1][r] : 0u);
        float o[16];
        zero<16>(o);
        wg_fence();
#pragma unroll
        for (int k = 0; k < 5; k++) wgmma_rs_n32(o, pa[k], dV + k * 112 + hh * 24, k);
        wg_commit();
        wg_wait<0>();
        reg_fence<16>(o);
        if (hh == 0) {
          stsm4(qa, pack2(o[0], o[1]), pack2(o[2], o[3]), pack2(o[4], o[5]), pack2(o[6], o[7]));
          stsm2(qa + 2048, pack2(o[8], o[9]), pack2(o[10], o[11]));
          o3a = pack2(o[12], o[13]); o3b = pack2(o[14], o[15]);
        } else {
          stsm4(qa + 3072, q < 2 ? o3a : pack2(o[0], o[1]), q < 2 ? o3b : pack2(o[2], o[3]), pack2(o[4], o[5]), pack2(o[6], o[7]));
          stsm4(qa + 5120, pack2(o[8], o[9]), pack2(o[10], o[11]), pack2(o[12], o[13]), pack2(o[14], o[15]));
        }
      }
      fence_async_smem();
      asm volatile("bar.sync 2, 128;" ::: "memory");
      if (tid == 256) {
        bulk_s2g(g_o + ((tb * 2 + mt) * 56 + 7 * j) * 64, sb + OFF_Q + mt * 8192, 7168);
        bulk_commit();
      }
      TSW(47 + 2 * mt);
    }
    if (tid == 256) {
      mbar_arrive_cluster(mapa(BAR(B_KVFREE), rank ^ 1));
      mbar_arrive(BAR(B_KVFREE));
      bulk_wait0();
      TS(50);
      flag_add(&g_oflag[tb * 8]);
      TS(51);
    }
  } else {
    asm volatile("setmaxnreg.dec.sync.aligned.u32 24;");
    if (warp == 12 && lane == 0) {
      prefetch_map(&p.wqkv);
      for (int i = 0; i < NST; i++) { mbar_init(BAR(B_FULL + i), 1); mbar_init(BAR(B_EMPTY + i), 4); }
      mbar_init(BAR(B_KV), 8);
      for (int i = 0; i < 2; i++) {
        mbar_init(BAR(B_Q + i), 4); mbar_init(BAR(B_H + i), 4); mbar_init(BAR(B_HFREE + i), 1); mbar_init(BAR(B_PART + i), 1);
        mbar_expect(BAR(B_PART + i), 14336);
      }
      mbar_init(BAR(B_KVFREE), 3); mbar_init(BAR(B_HALO), 1); mbar_init(BAR(B_GO), 1); mbar_init(BAR(B_XFREE), 16); mbar_init(BAR(B_WOK), 1);
      if (rank == 1) mbar_expect(BAR(B_HALO), 3584);
      asm volatile("fence.mbarrier_init.release.cluster;" ::: "memory");
    }
    __syncwarp();
    asm volatile("barrier.cluster.arrive.relaxed.aligned;" ::: "memory");
    asm volatile("barrier.cluster.wait.acquire.aligned;" ::: "memory");

    if (warp == 12) {
      if (lane == 0) {
        TS(52);
        prefetch_map(&p.wg32); prefetch_map(&p.wu32); prefetch_map(rank ? &p.wu : &p.wg); prefetch_map(&p.outm);
        Ring rg{0, 1};
        const int fbase = (j >> 2) * 896;
        const int cq = j * 56 - (j & 1) * 8;
        int i = 0;
#pragma unroll 1
        for (int ps = 0; ps < 5; ps++) {
          const CUtensorMap* m = ps < 2 ? &p.wqkv : (rank ? &p.wu : &p.wg);
          const int c0 = ps == 0 ? cq + D_ + D_ * rank : (ps == 1 ? cq : fbase + (4 * (ps - 2) + qn) * 64);
          if (ps == 1) mbar_wait(BAR(B_XFREE), 0);
#pragma unroll 1
          for (int kt = 0; kt < 7; kt++, i++) {
            if (i >= NST) mbar_wait(BAR(B_EMPTY + rg.st), rg.ph);
            const uint32_t fb = BAR(B_FULL + rg.st), dst = sb + rg.st * STAGE + rank * 8192;
            mbar_expect(fb, STAGE);
            if (ps == 1 && rank == 1) { tma2d_mc(dst, &p.wg32, fb, fbase + 768 + qn * 32, kt * 64); tma2d_mc(dst + 4096, &p.wu32, fb, fbase + 768 + qn * 32, kt * 64); }
            else tma2d_mc(dst, m, fb, c0, kt * 64);
            rg.next();
            if (i == 35 - NST) mbar_arrive(BAR(B_GO));
          }
        }
        TS(53);
        mbar_wait(BAR(B_WOK), 0);
        fence_async_global();
        TS(68);
        const uint4* wsrc = g_wd + (qn * 28 + rank * 14) * 896;
#pragma unroll 1
        for (int kt = 0; kt < 14; kt++) {
          rg.next();
          const int box = kt < 2 ? 12 + kt : kt - 2;
          mbar_wait(BAR(B_EMPTY + rg.st), rg.ph);
          const uint32_t fb = BAR(B_FULL + rg.st);
          mbar_expect(fb, 14336);
          bulk_g2s(sb + rg.st * STAGE, wsrc + box * 896, 14336, fb);
          rg.next();
        }
        wsrc = g_wo + (2 * qn + rank) * 3136;
#pragma unroll 1
        for (int kt = 0; kt < 4; kt++) {
          mbar_wait(BAR(B_EMPTY + rg.st), rg.ph);
          const uint32_t fb = BAR(B_FULL + rg.st);
          const int bytes = kt < 3 ? 14336 : 7168;
          mbar_expect(fb, bytes);
          bulk_g2s(sb + rg.st * STAGE, wsrc + kt * 896, bytes, fb);
          rg.next(); rg.next(); rg.next();
        }
        TS(54);
      }
    } else if (warp == 13) {
      const uint32_t epoch = *(volatile uint32_t*)&g_epoch[blockIdx.x * 8] + 1;
      if (tb == 0) {
        mbar_wait(BAR(B_XFREE), 0);
#pragma unroll
        for (int i = 0; i < 7; i++) {
          const int c = i * 32 + lane;
          sts128(sb + (c < 112 ? OFF_K + c * 16 : OFF_V + (c - 112) * 16), make_uint4(0, 0, 0, 0));
        }
        fence_async_smem();
        __syncwarp();
        if (lane == 0) mbar_arrive(BAR(B_HALO));
      } else if (rank == 0) {
        if (lane == 0) {
          mbar_wait(BAR(B_KV), 0);
          const uint32_t* f = &g_haloflag[((tb - 1) * 8 + j) * 8];
          int it = 0;
          while ((int32_t)(ld_flag(f) - epoch) < 0) { if (++it > (1 << 20)) __trap(); }
          fence_async_global();
          const uint4* src = g_halo + ((tb - 1) * 8 + j) * 224;
          mbar_expect(BAR(B_HALO), 3584);
          bulk_g2s(sb + OFF_K, src, 1792, BAR(B_HALO));
          bulk_g2s(sb + OFF_V, src + 112, 1792, BAR(B_HALO));
          TS(55);
        }
        __syncwarp();
      }
      const int k = lane < 21 ? lane : 20;
      const int box = k < 2 ? 12 + k : k - 2;
      const int step = k < 14 ? 35 + 2 * k : 64 + (k - 14) + ((k - 14) >> 1);
      const uint32_t* flag = k < 14 ? &g_hflag[((T2 * 2 + rank) * 14 + box) * 8] : &g_oflag[T2 * 8];
      const uint32_t target = epoch * (k < 2 ? 4 : (k < 14 ? 2 : 8));
      if (lane == 0) {
        int it = 0;
        mbar_wait(BAR(B_Q), 0);
        while ((int32_t)(ld_flag(g_wflag) - epoch * 128) < 0) { if (++it > (1 << 20)) __trap(); }
        mbar_arrive(BAR(B_WOK));
      }
      __syncwarp();
      mbar_wait(BAR(B_GO), 0);
      mbar_wait(BAR(B_EMPTY + 35 % NST), ((35 / NST) & 1) ^ 1);
      int next = 0, it = 0;
      uint32_t ready = 0;
      while (true) {
        if (!((ready >> lane) & 1)) {
          const bool ok = (int32_t)(ld_flag(flag) - target) >= 0;
          if (ok) fence_async_global();
          ready = ok ? (1u << lane) : 0u;
        } else ready = 1u << lane;
        ready = __reduce_or_sync(~0u, ready);
        while (next < 21 && ((ready >> next) & 1)) {
          if (lane == next) {
            const uint32_t st = step % NST;
            mbar_wait(BAR(B_EMPTY + st), ((step / NST) & 1) ^ 1);
            const uint32_t fb = BAR(B_FULL + st);
            mbar_expect(fb, STAGE);
            if (k < 14) bulk_g2s(sb + st * STAGE, g_h + ((T2 * 2 + rank) * 14 + box) * 1024, STAGE, fb);
            else {
              const uint4* src = g_o + (T2 * 112 + (k - 14) * 8) * 64;
              bulk_g2s(sb + st * STAGE, src, 8192, fb);
              bulk_g2s(sb + st * STAGE + 8192, src + 56 * 64, 8192, fb);
            }
            if (k == 0) TS(56);
            if (k == 10) TS(57);
            if (k == 13) TS(58);
            if (k == 20) TS(59);
          }
          __syncwarp();
          next++;
        }
        if (next == 21) break;
        if (++it > (1 << 20)) __trap();
      }
      if (lane == 0) g_epoch[blockIdx.x * 8] = epoch;
    } else if (lane == 0) {
      const int w = warp - 14;
      if (w == 1) {
        mbar_wait(BAR(B_KV), 0);
        if (rank == 0) {
          const uint32_t hb = mapa(BAR(B_HALO), 1);
          bulk_s2s(mapa(sb + OFF_K, 1), sb + OFF_K + 16 * 896, 1792, hb);
          bulk_s2s(mapa(sb + OFF_V, 1), sb + OFF_V + 16 * 896, 1792, hb);
        } else if (tb < 15) {
          uint4* dst = g_halo + (tb * 8 + j) * 224;
          bulk_s2g(dst, sb + OFF_K + 16 * 896, 1792);
          bulk_s2g(dst + 112, sb + OFF_V + 16 * 896, 1792);
          bulk_commit();
          bulk_wait0();
          flag_add(&g_haloflag[(tb * 8 + j) * 8]);
          TS(60);
        }
        mbar_arrive_cluster(mapa(BAR(B_KVFREE), rank ^ 1));
      }
      const int hb = (tb * 2 + (j >> 2)) * 14;
#pragma unroll 1
      for (int ps = 0; ps < 4; ps++) {
        const int box = ps == 0 ? 12 + (qn >> 1) : 4 * (ps - 1) + qn;
        mbar_wait(BAR(B_H + w), ps & 1);
        bulk_s2g(g_h + (hb + box) * 1024 + w * 512 + (ps == 0 ? (qn & 1) * 256 : 0), sb + OFF_HS + w * 8192, ps == 0 ? 4096 : 8192);
        bulk_commit();
        bulk_wait0();
        if (ps == 3) TS(61 + w);
        mbar_arrive(BAR(B_HFREE + w));
        flag_add(&g_hflag[(hb + box) * 8]);
        if (ps >= 2) TS(63 + 2 * (ps - 2) + w);
      }
    }
  }
#undef BAR
}

typedef CUresult (*EncFn)(CUtensorMap*, CUtensorMapDataType, cuuint32_t, void*, const cuuint64_t*, const cuuint64_t*,
                          const cuuint32_t*, const cuuint32_t*, CUtensorMapInterleave, CUtensorMapSwizzle,
                          CUtensorMapL2promotion, CUtensorMapFloatOOBfill);

void enc2d(EncFn enc, CUtensorMap* m, const void* ptr, int cols, int rows, int bc, int br, CUtensorMapSwizzle sw) {
  cuuint64_t gd[2] = {(cuuint64_t)cols, (cuuint64_t)rows};
  cuuint64_t gs[1] = {(cuuint64_t)cols * 2};
  cuuint32_t bd[2] = {(cuuint32_t)bc, (cuuint32_t)br}, es[2] = {1, 1};
  enc(m, CU_TENSOR_MAP_DATA_TYPE_BFLOAT16, 2, const_cast<void*>(ptr), gd, gs, bd, es, CU_TENSOR_MAP_INTERLEAVE_NONE, sw,
      CU_TENSOR_MAP_L2_PROMOTION_L2_128B, CU_TENSOR_MAP_FLOAT_OOB_FILL_NONE);
}

}

extern "C" void kernel_launch(void* const* d_in, const int* in_sizes, int n_in, void* d_out, int out_size) {
  static EncFn enc = nullptr;
  if (!enc) {
    void* fn = nullptr;
    cudaDriverEntryPointQueryResult qr;
    cudaGetDriverEntryPoint("cuTensorMapEncodeTiled", &fn, cudaEnableDefault, &qr);
    enc = (EncFn)fn;
    cudaFuncSetAttribute(fused_kernel, cudaFuncAttributeMaxDynamicSharedMemorySize, SMEM_BYTES);
  }
  Params p;
  enc2d(enc, &p.xm, d_in[0], D_, S_, 64, 64, CU_TENSOR_MAP_SWIZZLE_128B);
  enc2d(enc, &p.wqkv, d_in[1], 3 * D_, D_, 64, 64, CU_TENSOR_MAP_SWIZZLE_128B);
  enc2d(enc, &p.wg, d_in[4], F_, D_, 64, 64, CU_TENSOR_MAP_SWIZZLE_128B);
  enc2d(enc, &p.wu, d_in[5], F_, D_, 64, 64, CU_TENSOR_MAP_SWIZZLE_128B);
  enc2d(enc, &p.wg32, d_in[4], F_, D_, 32, 64, CU_TENSOR_MAP_SWIZZLE_64B);
  enc2d(enc, &p.wu32, d_in[5], F_, D_, 32, 64, CU_TENSOR_MAP_SWIZZLE_64B);
  enc2d(enc, &p.outm, d_out, D_, S_, 56, 16, CU_TENSOR_MAP_SWIZZLE_NONE);
  p.x = (const __nv_bfloat16*)d_in[0];
  p.wd = (const uint4*)d_in[6];
  p.wo = (const uint4*)d_in[2];
  fused_kernel<<<128, 512, SMEM_BYTES>>>(p);
}
```

```cpp
#include <cuda_runtime.h>
#include <cuda_bf16.h>
#include <cuda.h>
#include <stdint.h>

namespace {

constexpr int S_ = 2048, D_ = 448, F_ = 1792;
constexpr int NST = 10;
constexpr int STAGE = 16384;
constexpr int KVB = 18 * 896;
constexpr int OFF_K = NST * STAGE;
constexpr int OFF_V = OFF_K + KVB;
constexpr int OFF_Q = OFF_V + KVB;
constexpr int OFF_HS = OFF_Q + 16384;
constexpr int OFF_WOB = OFF_K;
constexpr int OFF_PART = OFF_K + 50176;
constexpr int OFF_BAR = 229376;
constexpr int OFF_ONES = OFF_BAR + 768;
constexpr int OFF_STAT = OFF_BAR + 1024;
constexpr int SMEM_BYTES = OFF_BAR + 2048;
constexpr int B_FULL = 0, B_HFREE = 10  , B_PART = 12  , B_HALO = 16, B_GO = 17, B_PFREE = 18,
              B_X = 19  , B_ORDY = 33, B_WOK = 34, B_KVFREE = 35, B_WOB = 36, B_HLAST = 37,
              B_FULL2 = 38  , B_EMPTY2 = 43  ,
              B_EMPTY = 48, B_Q = 58  , B_H = 60  ,
              B_KV = 62, B_XFREE = 63  , B_DONE = 65;
#define LAG0 2
#define LAGA 6
#define LAGB 6
#define LAGD 6

struct Params {
  CUtensorMap xm, wqkv, wg, wu, wg32, wu32, outm, xr;
};

struct Scratch {
  uint4 h[S_ * F_ / 8];
  uint4 o[S_ * D_ / 8];
  uint4 wd[F_ * D_ / 8];
  uint4 wo[D_ * D_ / 8];
  uint4 halo[16 * 8 * 224];
  uint32_t flag[(448 + 16 + 1 + 128 + 128) * 8];
};
constexpr int F_H = 0, F_O = 448, F_W = 464, F_HALO = 465, F_EPOCH = 593;
__device__ Scratch g_s;
#define TS(slot)
#define TG(slot)
#define TSW(slot)

__device__ __forceinline__ uint32_t s2u(const void* p) { return (uint32_t)__cvta_generic_to_shared(p); }
__device__ __forceinline__ void mbar_init(uint32_t b, int c) { asm volatile("mbarrier.init.shared::cta.b64 [%0], %1;" ::"r"(b), "r"(c) : "memory"); }
__device__ __forceinline__ void mbar_expect(uint32_t b, int bytes) { asm volatile("mbarrier.arrive.expect_tx.shared::cta.b64 _, [%0], %1;" ::"r"(b), "r"(bytes) : "memory"); }
__device__ __forceinline__ void mbar_arrive(uint32_t b) { asm volatile("mbarrier.arrive.shared::cta.b64 _, [%0];" ::"r"(b) : "memory"); }
__device__ __forceinline__ void mbar_arrive_cluster(uint32_t b) { asm volatile("mbarrier.arrive.shared::cluster.b64 _, [%0];" ::"r"(b) : "memory"); }
__device__ __forceinline__ uint32_t mapa(uint32_t a, uint32_t r) { uint32_t o; asm volatile("mapa.shared::cluster.u32 %0, %1, %2;" : "=r"(o) : "r"(a), "r"(r)); return o; }
__device__ __forceinline__ void mbar_wait(uint32_t b, uint32_t ph) {
  asm volatile("{\n.reg .pred p;\nW: mbarrier.try_wait.parity.shared::cta.b64 p, [%0], %1;\n@!p bra W;\n}" ::"r"(b), "r"(ph) : "memory");
}
__device__ __forceinline__ void mbar_wait_lim(uint32_t b, uint32_t ph) {
  uint32_t ok;
  int it = 0;
  do {
    if (++it > (1 << 18)) __trap();
    asm volatile("{.reg .pred p; mbarrier.try_wait.parity.shared::cta.b64 p, [%1], %2; selp.u32 %0,1,0,p;}" : "=r"(ok) : "r"(b), "r"(ph) : "memory");
  } while (!ok);
}
__device__ __forceinline__ uint32_t ld_flag(const uint32_t* f) { uint32_t v; asm volatile("ld.relaxed.gpu.global.u32 %0, [%1];" : "=r"(v) : "l"(f) : "memory"); return v; }
__device__ __forceinline__ void flag_add(uint32_t* f) { asm volatile("red.relaxed.gpu.global.add.u32 [%0], 1;" ::"l"(f) : "memory"); }
__device__ __forceinline__ void flag_add_rel(uint32_t* f) { asm volatile("red.release.gpu.global.add.u32 [%0], 1;" ::"l"(f) : "memory"); }
__device__ __forceinline__ void fence_async_smem() { asm volatile("fence.proxy.async.shared::cta;" ::: "memory"); }
__device__ __forceinline__ void fence_async_global() { asm volatile("fence.proxy.async.global;" ::: "memory"); }

__device__ __forceinline__ void tma2d(uint32_t dst, const CUtensorMap* m, uint32_t bar, int c0, int c1) {
  asm volatile("cp.async.bulk.tensor.2d.shared::cluster.global.mbarrier::complete_tx::bytes [%0], [%1, {%3,%4}], [%2];" ::"r"(dst), "l"(m), "r"(bar), "r"(c0), "r"(c1) : "memory");
}
__device__ __forceinline__ void tma2d_mc(uint32_t dst, const CUtensorMap* m, uint32_t bar, int c0, int c1) {
  asm volatile("cp.async.bulk.tensor.2d.shared::cluster.global.mbarrier::complete_tx::bytes.multicast::cluster [%0], [%1, {%3,%4}], [%2], %5;" ::"r"(dst), "l"(m), "r"(bar), "r"(c0), "r"(c1), "h"((uint16_t)3) : "memory");
}
__device__ __forceinline__ void bulk_g2s(uint32_t dst, const void* src, int bytes, uint32_t bar) {
  asm volatile("cp.async.bulk.shared::cluster.global.mbarrier::complete_tx::bytes [%0], [%1], %2, [%3];" ::"r"(dst), "l"(src), "r"(bytes), "r"(bar) : "memory");
}
__device__ __forceinline__ void bulk_s2g(void* dst, uint32_t src, int bytes) {
  asm volatile("cp.async.bulk.global.shared::cta.bulk_group [%0], [%1], %2;" ::"l"(dst), "r"(src), "r"(bytes) : "memory");
}
__device__ __forceinline__ void bulk_s2s(uint32_t dst, uint32_t src, int bytes, uint32_t bar) {
  asm volatile("cp.async.bulk.shared::cluster.shared::cta.mbarrier::complete_tx::bytes [%0], [%1], %2, [%3];" ::"r"(dst), "r"(src), "r"(bytes), "r"(bar) : "memory");
}
__device__ __forceinline__ void bulk_commit() { asm volatile("cp.async.bulk.commit_group;" ::: "memory"); }
__device__ __forceinline__ void bulk_wait0() { asm volatile("cp.async.bulk.wait_group 0;" ::: "memory"); }
__device__ __forceinline__ void bulk_wait0_read() { asm volatile("cp.async.bulk.wait_group.read 0;" ::: "memory"); }
__device__ __forceinline__ void prefetch_map(const CUtensorMap* m) { asm volatile("prefetch.tensormap [%0];" ::"l"(m) : "memory"); }

__device__ __forceinline__ void ldsm4(uint32_t* r, uint32_t a) { asm volatile("ldmatrix.sync.aligned.m8n8.x4.shared.b16 {%0,%1,%2,%3}, [%4];" : "=r"(r[0]), "=r"(r[1]), "=r"(r[2]), "=r"(r[3]) : "r"(a) : "memory"); }
__device__ __forceinline__ void stsm4(uint32_t a, uint32_t r0, uint32_t r1, uint32_t r2, uint32_t r3) { asm volatile("stmatrix.sync.aligned.m8n8.x4.shared.b16 [%0], {%1,%2,%3,%4};" ::"r"(a), "r"(r0), "r"(r1), "r"(r2), "r"(r3) : "memory"); }
__device__ __forceinline__ void stsm2(uint32_t a, uint32_t r0, uint32_t r1) { asm volatile("stmatrix.sync.aligned.m8n8.x2.shared.b16 [%0], {%1,%2};" ::"r"(a), "r"(r0), "r"(r1) : "memory"); }
__device__ __forceinline__ uint32_t pack2(float lo, float hi) { uint32_t r; asm("cvt.rn.bf16x2.f32 %0, %1, %2;" : "=r"(r) : "f"(hi), "f"(lo)); return r; }
__device__ __forceinline__ float bf_lo(uint32_t v) { return __uint_as_float(v << 16); }
__device__ __forceinline__ float bf_hi(uint32_t v) { return __uint_as_float(v & 0xffff0000u); }
__device__ __forceinline__ float rbf(float v) { return bf_lo(pack2(v, 0.f)); }
__device__ __forceinline__ float lds32f(uint32_t a) { float v; asm volatile("ld.shared.f32 %0, [%1];" : "=f"(v) : "r"(a) : "memory"); return v; }
__device__ __forceinline__ uint32_t sub2(uint32_t a, uint32_t b) { uint32_t r; asm("sub.rn.bf16x2 %0, %1, %2;" : "=r"(r) : "r"(a), "r"(b)); return r; }
__device__ __forceinline__ uint32_t add2(uint32_t a, uint32_t b) { uint32_t r; asm("add.rn.bf16x2 %0, %1, %2;" : "=r"(r) : "r"(a), "r"(b)); return r; }
__device__ __forceinline__ uint32_t mul2(uint32_t a, uint32_t b) { uint32_t r; asm("mul.rn.bf16x2 %0, %1, %2;" : "=r"(r) : "r"(a), "r"(b)); return r; }
__device__ __forceinline__ float ex2(float v) { float r; asm("ex2.approx.ftz.f32 %0, %1;" : "=f"(r) : "f"(v)); return r; }
__device__ __forceinline__ float sqrt_approx(float v) { float r; asm("sqrt.approx.ftz.f32 %0, %1;" : "=f"(r) : "f"(v)); return r; }
__device__ __forceinline__ float rcp(float v) { float r; asm("rcp.approx.ftz.f32 %0, %1;" : "=f"(r) : "f"(v)); return r; }
__device__ __forceinline__ uint4 lds128(uint32_t a) { uint4 v; asm volatile("ld.shared.v4.u32 {%0,%1,%2,%3}, [%4];" : "=r"(v.x), "=r"(v.y), "=r"(v.z), "=r"(v.w) : "r"(a) : "memory"); return v; }
__device__ __forceinline__ void lds128v(uint32_t* v, uint32_t a) { asm volatile("ld.shared.v4.u32 {%0,%1,%2,%3}, [%4];" : "=r"(v[0]), "=r"(v[1]), "=r"(v[2]), "=r"(v[3]) : "r"(a) : "memory"); }
__device__ __forceinline__ void sts128(uint32_t a, uint4 v) { asm volatile("st.shared.v4.u32 [%0], {%1,%2,%3,%4};" ::"r"(a), "r"(v.x), "r"(v.y), "r"(v.z), "r"(v.w) : "memory"); }
__device__ __forceinline__ uint4 ldg128(const void* p) { uint4 v; asm volatile("ld.global.nc.L1::no_allocate.v4.u32 {%0,%1,%2,%3}, [%4];" : "=r"(v.x), "=r"(v.y), "=r"(v.z), "=r"(v.w) : "l"(p)); return v; }

__device__ __forceinline__ void wg_fence() { asm volatile("wgmma.fence.sync.aligned;" ::: "memory"); }
__device__ __forceinline__ void wg_commit() { asm volatile("wgmma.commit_group.sync.aligned;" ::: "memory"); }
template <int N> __device__ __forceinline__ void wg_wait() { asm volatile("wgmma.wait_group.sync.aligned %0;" ::"n"(N) : "memory"); }
template <int N> __device__ __forceinline__ void reg_fence(float* d) {
#pragma unroll
  for (int i = 0; i < N; i++) asm volatile("" : "+f"(d[i])::"memory");
}
template <int N> __device__ __forceinline__ void zero(float* d) {
#pragma unroll
  for (int i = 0; i < N; i++) d[i] = 0.f;
}
__device__ __forceinline__ uint64_t mkdesc(uint32_t addr, uint32_t lbo, uint32_t sbo, uint32_t sw) {
  return (uint64_t)((addr & 0x3FFFF) >> 4) | ((uint64_t)(lbo >> 4) << 16) | ((uint64_t)(sbo >> 4) << 32) | ((uint64_t)sw << 62);
}

__device__ __forceinline__ void wgmma_ss_n8(float* d, uint64_t da, uint64_t db, int sd) {
  asm volatile("{\n.reg .pred p;\nsetp.ne.b32 p, %6, 0;\nwgmma.mma_async.sync.aligned.m64n8k16.f32.bf16.bf16 {%0,%1,%2,%3}, %4, %5, p, 1, 1, 0, 1;\n}\n"
    : "+f"(d[0]),"+f"(d[1]),"+f"(d[2]),"+f"(d[3])
    : "l"(da),"l"(db),"r"(sd));
}
__device__ __forceinline__ void wgmma_rs_n56(float* d, const uint32_t* a, uint64_t db, int sd) {
  asm volatile("{\n.reg .pred p;\nsetp.ne.b32 p, %33, 0;\nwgmma.mma_async.sync.aligned.m64n56k16.f32.bf16.bf16 {%0,%1,%2,%3,%4,%5,%6,%7,%8,%9,%10,%11,%12,%13,%14,%15,%16,%17,%18,%19,%20,%21,%22,%23,%24,%25,%26,%27}, {%28,%29,%30,%31}, %32, p, 1, 1, 1;\n}\n"
    : "+f"(d[0]),"+f"(d[1]),"+f"(d[2]),"+f"(d[3]),"+f"(d[4]),"+f"(d[5]),"+f"(d[6]),"+f"(d[7]),"+f"(d[8]),"+f"(d[9]),"+f"(d[10]),"+f"(d[11]),"+f"(d[12]),"+f"(d[13]),"+f"(d[14]),"+f"(d[15]),"+f"(d[16]),"+f"(d[17]),"+f"(d[18]),"+f"(d[19]),"+f"(d[20]),"+f"(d[21]),"+f"(d[22]),"+f"(d[23]),"+f"(d[24]),"+f"(d[25]),"+f"(d[26]),"+f"(d[27])
    : "r"(a[0]),"r"(a[1]),"r"(a[2]),"r"(a[3]),"l"(db),"r"(sd));
}
__device__ __forceinline__ void wgmma_rs_n64(float* d, const uint32_t* a, uint64_t db, int sd) {
  asm volatile("{\n.reg .pred p;\nsetp.ne.b32 p, %37, 0;\nwgmma.mma_async.sync.aligned.m64n64k16.f32.bf16.bf16 {%0,%1,%2,%3,%4,%5,%6,%7,%8,%9,%10,%11,%12,%13,%14,%15,%16,%17,%18,%19,%20,%21,%22,%23,%24,%25,%26,%27,%28,%29,%30,%31}, {%32,%33,%34,%35}, %36, p, 1, 1, 1;\n}\n"
    : "+f"(d[0]),"+f"(d[1]),"+f"(d[2]),"+f"(d[3]),"+f"(d[4]),"+f"(d[5]),"+f"(d[6]),"+f"(d[7]),"+f"(d[8]),"+f"(d[9]),"+f"(d[10]),"+f"(d[11]),"+f"(d[12]),"+f"(d[13]),"+f"(d[14]),"+f"(d[15]),"+f"(d[16]),"+f"(d[17]),"+f"(d[18]),"+f"(d[19]),"+f"(d[20]),"+f"(d[21]),"+f"(d[22]),"+f"(d[23]),"+f"(d[24]),"+f"(d[25]),"+f"(d[26]),"+f"(d[27]),"+f"(d[28]),"+f"(d[29]),"+f"(d[30]),"+f"(d[31])
    : "r"(a[0]),"r"(a[1]),"r"(a[2]),"r"(a[3]),"l"(db),"r"(sd));
}
__device__ __forceinline__ void wgmma_rs_n128(float* d, const uint32_t* a, uint64_t db, int sd) {
  asm volatile("{\n.reg .pred p;\nsetp.ne.b32 p, %69, 0;\nwgmma.mma_async.sync.aligned.m64n128k16.f32.bf16.bf16 {%0,%1,%2,%3,%4,%5,%6,%7,%8,%9,%10,%11,%12,%13,%14,%15,%16,%17,%18,%19,%20,%21,%22,%23,%24,%25,%26,%27,%28,%29,%30,%31,%32,%33,%34,%35,%36,%37,%38,%39,%40,%41,%42,%43,%44,%45,%46,%47,%48,%49,%50,%51,%52,%53,%54,%55,%56,%57,%58,%59,%60,%61,%62,%63}, {%64,%65,%66,%67}, %68, p, 1, 1, 1;\n}\n"
    : "+f"(d[0]),"+f"(d[1]),"+f"(d[2]),"+f"(d[3]),"+f"(d[4]),"+f"(d[5]),"+f"(d[6]),"+f"(d[7]),"+f"(d[8]),"+f"(d[9]),"+f"(d[10]),"+f"(d[11]),"+f"(d[12]),"+f"(d[13]),"+f"(d[14]),"+f"(d[15]),"+f"(d[16]),"+f"(d[17]),"+f"(d[18]),"+f"(d[19]),"+f"(d[20]),"+f"(d[21]),"+f"(d[22]),"+f"(d[23]),"+f"(d[24]),"+f"(d[25]),"+f"(d[26]),"+f"(d[27]),"+f"(d[28]),"+f"(d[29]),"+f"(d[30]),"+f"(d[31]),"+f"(d[32]),"+f"(d[33]),"+f"(d[34]),"+f"(d[35]),"+f"(d[36]),"+f"(d[37]),"+f"(d[38]),"+f"(d[39]),"+f"(d[40]),"+f"(d[41]),"+f"(d[42]),"+f"(d[43]),"+f"(d[44]),"+f"(d[45]),"+f"(d[46]),"+f"(d[47]),"+f"(d[48]),"+f"(d[49]),"+f"(d[50]),"+f"(d[51]),"+f"(d[52]),"+f"(d[53]),"+f"(d[54]),"+f"(d[55]),"+f"(d[56]),"+f"(d[57]),"+f"(d[58]),"+f"(d[59]),"+f"(d[60]),"+f"(d[61]),"+f"(d[62]),"+f"(d[63])
    : "r"(a[0]),"r"(a[1]),"r"(a[2]),"r"(a[3]),"l"(db),"r"(sd));
}
__device__ __forceinline__ void wgmma_ss_n112(float* d, uint64_t da, uint64_t db, int sd) {
  asm volatile("{\n.reg .pred p;\nsetp.ne.b32 p, %58, 0;\nwgmma.mma_async.sync.aligned.m64n112k16.f32.bf16.bf16 {%0,%1,%2,%3,%4,%5,%6,%7,%8,%9,%10,%11,%12,%13,%14,%15,%16,%17,%18,%19,%20,%21,%22,%23,%24,%25,%26,%27,%28,%29,%30,%31,%32,%33,%34,%35,%36,%37,%38,%39,%40,%41,%42,%43,%44,%45,%46,%47,%48,%49,%50,%51,%52,%53,%54,%55}, %56, %57, p, 1, 1, 0, 1;\n}\n"
    : "+f"(d[0]),"+f"(d[1]),"+f"(d[2]),"+f"(d[3]),"+f"(d[4]),"+f"(d[5]),"+f"(d[6]),"+f"(d[7]),"+f"(d[8]),"+f"(d[9]),"+f"(d[10]),"+f"(d[11]),"+f"(d[12]),"+f"(d[13]),"+f"(d[14]),"+f"(d[15]),"+f"(d[16]),"+f"(d[17]),"+f"(d[18]),"+f"(d[19]),"+f"(d[20]),"+f"(d[21]),"+f"(d[22]),"+f"(d[23]),"+f"(d[24]),"+f"(d[25]),"+f"(d[26]),"+f"(d[27]),"+f"(d[28]),"+f"(d[29]),"+f"(d[30]),"+f"(d[31]),"+f"(d[32]),"+f"(d[33]),"+f"(d[34]),"+f"(d[35]),"+f"(d[36]),"+f"(d[37]),"+f"(d[38]),"+f"(d[39]),"+f"(d[40]),"+f"(d[41]),"+f"(d[42]),"+f"(d[43]),"+f"(d[44]),"+f"(d[45]),"+f"(d[46]),"+f"(d[47]),"+f"(d[48]),"+f"(d[49]),"+f"(d[50]),"+f"(d[51]),"+f"(d[52]),"+f"(d[53]),"+f"(d[54]),"+f"(d[55])
    : "l"(da),"l"(db),"r"(sd));
}
__device__ __forceinline__ void wgmma_ss_n56(float* d, uint64_t da, uint64_t db, int sd) {
  asm volatile("{\n.reg .pred p;\nsetp.ne.b32 p, %30, 0;\nwgmma.mma_async.sync.aligned.m64n56k16.f32.bf16.bf16 {%0,%1,%2,%3,%4,%5,%6,%7,%8,%9,%10,%11,%12,%13,%14,%15,%16,%17,%18,%19,%20,%21,%22,%23,%24,%25,%26,%27}, %28, %29, p, 1, 1, 0, 1;\n}\n"
    : "+f"(d[0]),"+f"(d[1]),"+f"(d[2]),"+f"(d[3]),"+f"(d[4]),"+f"(d[5]),"+f"(d[6]),"+f"(d[7]),"+f"(d[8]),"+f"(d[9]),"+f"(d[10]),"+f"(d[11]),"+f"(d[12]),"+f"(d[13]),"+f"(d[14]),"+f"(d[15]),"+f"(d[16]),"+f"(d[17]),"+f"(d[18]),"+f"(d[19]),"+f"(d[20]),"+f"(d[21]),"+f"(d[22]),"+f"(d[23]),"+f"(d[24]),"+f"(d[25]),"+f"(d[26]),"+f"(d[27])
    : "l"(da),"l"(db),"r"(sd));
}
__device__ __forceinline__ void wgmma_ssk_n80(float* d, uint64_t da, uint64_t db, int sd) {
  asm volatile("{\n.reg .pred p;\nsetp.ne.b32 p, %42, 0;\nwgmma.mma_async.sync.aligned.m64n80k16.f32.bf16.bf16 {%0,%1,%2,%3,%4,%5,%6,%7,%8,%9,%10,%11,%12,%13,%14,%15,%16,%17,%18,%19,%20,%21,%22,%23,%24,%25,%26,%27,%28,%29,%30,%31,%32,%33,%34,%35,%36,%37,%38,%39}, %40, %41, p, 1, 1, 0, 0;\n}\n"
    : "+f"(d[0]),"+f"(d[1]),"+f"(d[2]),"+f"(d[3]),"+f"(d[4]),"+f"(d[5]),"+f"(d[6]),"+f"(d[7]),"+f"(d[8]),"+f"(d[9]),"+f"(d[10]),"+f"(d[11]),"+f"(d[12]),"+f"(d[13]),"+f"(d[14]),"+f"(d[15]),"+f"(d[16]),"+f"(d[17]),"+f"(d[18]),"+f"(d[19]),"+f"(d[20]),"+f"(d[21]),"+f"(d[22]),"+f"(d[23]),"+f"(d[24]),"+f"(d[25]),"+f"(d[26]),"+f"(d[27]),"+f"(d[28]),"+f"(d[29]),"+f"(d[30]),"+f"(d[31]),"+f"(d[32]),"+f"(d[33]),"+f"(d[34]),"+f"(d[35]),"+f"(d[36]),"+f"(d[37]),"+f"(d[38]),"+f"(d[39])
    : "l"(da),"l"(db),"r"(sd));
}
__device__ __forceinline__ void wgmma_rs_n32(float* d, const uint32_t* a, uint64_t db, int sd) {
  asm volatile("{\n.reg .pred p;\nsetp.ne.b32 p, %21, 0;\nwgmma.mma_async.sync.aligned.m64n32k16.f32.bf16.bf16 {%0,%1,%2,%3,%4,%5,%6,%7,%8,%9,%10,%11,%12,%13,%14,%15}, {%16,%17,%18,%19}, %20, p, 1, 1, 1;\n}\n"
    : "+f"(d[0]),"+f"(d[1]),"+f"(d[2]),"+f"(d[3]),"+f"(d[4]),"+f"(d[5]),"+f"(d[6]),"+f"(d[7]),"+f"(d[8]),"+f"(d[9]),"+f"(d[10]),"+f"(d[11]),"+f"(d[12]),"+f"(d[13]),"+f"(d[14]),"+f"(d[15])
    : "r"(a[0]),"r"(a[1]),"r"(a[2]),"r"(a[3]),"l"(db),"r"(sd));
}

constexpr float LOG2E = 1.4426950408889634f;

__device__ __forceinline__ uint32_t swiglu2(float g0, float u0, float g1, float u1, float c1, float k) {
  return pack2((g0 * u0) * rcp(fmaf(ex2(g0 * c1), k, k)), (g1 * u1) * rcp(fmaf(ex2(g1 * c1), k, k)));
}
__device__ __forceinline__ uint32_t gate2(float a0, float a1, uint32_t pv) {
  const float f0 = a0 + bf_lo(pv), f1 = a1 + bf_hi(pv);
  const float d0 = 1.f + ex2(fminf(f0 * -LOG2E, 60.f)), d1 = 1.f + ex2(fminf(f1 * -LOG2E, 60.f));
  const float r = rcp(d0 * d1);
  return pack2((f0 * d1) * r, (f1 * d0) * r);
}

__device__ __forceinline__ void row_stats(uint32_t sb, int h, int r, int lane) {
  const uint32_t row = sb + (h ? 7 * STAGE : OFF_K) + r * 128 + ((((lane & 1) * 4) ^ (r & 7)) << 4);
  float e[4] = {0.f, 0.f, 0.f, 0.f}, m[4] = {0.f, 0.f, 0.f, 0.f};
#pragma unroll 1
  for (int t = 0; t < 7; t++) {
    mbar_wait(sb + OFF_BAR + 8 * (B_X + h * 7 + t), 0);
    const uint32_t ra = row + t * 8192 + (t == 6 ? h * 57344 : 0);
    uint4 v[4];
#pragma unroll
    for (int c = 0; c < 4; c++) v[c] = lds128(ra ^ (c << 4));
#pragma unroll
    for (int c = 0; c < 4; c++) {
      const uint32_t u[4] = {v[c].x, v[c].y, v[c].z, v[c].w};
#pragma unroll
      for (int i = 0; i < 4; i++) { e[i] = fmaf(bf_lo(u[i]), bf_lo(u[i]), e[i]); m[i] += bf_lo(u[i]); }
#pragma unroll
      for (int i = 0; i < 4; i++) { e[i] = fmaf(bf_hi(u[i]), bf_hi(u[i]), e[i]); m[i] += bf_hi(u[i]); }
    }
  }
  float es = (e[0] + e[1]) + (e[2] + e[3]), ms = (m[0] + m[1]) + (m[2] + m[3]);
  es += __shfl_xor_sync(~0u, es, 1); ms += __shfl_xor_sync(~0u, ms, 1);
  ms *= 1.f / D_;
  const float sd = rbf(sqrt_approx(rbf(rbf(fmaxf(fmaf(-ms, ms, es * (1.f / D_)), 0.f)) + 1e-5f)));
  asm volatile("st.shared.v2.f32 [%0], {%1,%2};" ::"r"(sb + OFF_STAT + (r + h * 64) * 8), "f"(ms), "f"(sd) : "memory");
  __syncwarp();
}

struct Ring {
  uint32_t st, ph;
  __device__ __forceinline__ void next() { if (++st == NST) { st = 0; ph ^= 1; } }
};

__global__ void __cluster_dims__(2, 1, 1) __launch_bounds__(512, 1) fused_kernel(Scratch* __restrict__ gs, const uint4* __restrict__ wd, const uint4* __restrict__ wo_in, const __grid_constant__ Params p) {
  extern __shared__ __align__(1024) uint8_t smem[];
  const uint32_t sb = s2u(smem);
  const uint32_t bars = sb + OFF_BAR;
  const int tid = threadIdx.x, warp = __shfl_sync(~0u, tid >> 5, 0), lane = tid & 31;
  const int rank = blockIdx.x & 1, cid = blockIdx.x >> 1;
  if (tid == 0) { TG(0); TS(1); }
  int grp, j;
  if (cid < 4) { grp = 0; j = 4 + cid; }
  else if (cid < 36) { grp = (cid - 4) & 7; j = (cid - 4) >> 3; }
  else { j = ((cid - 36) * 37) >> 8; grp = 1 + (cid - 36) - 7 * j; j += 4; }
  const int tb = 2 * grp + rank;
  const int T2 = 2 * grp + (j >> 2);
  const int qn = j & 3;
#define BAR(i) (bars + 8 * (i))
  const int wg = warp >> 2;
  if (warp < 12) {
  asm volatile("barrier.cluster.arrive.relaxed.aligned;" ::: "memory");
  if (warp >= 4) asm volatile("barrier.cluster.wait.acquire.aligned;" ::: "memory");
  const uint32_t xs = sb + (wg == 0 ? OFF_K : 7 * STAGE);
  if (warp < 8) {
    if (lane == 0) {
      const int w = warp & 3;
      const uint32_t b0 = BAR(B_X + wg * 7 + w);
      mbar_init(b0, 1);
      if (w < 3) mbar_init(b0 + 32, 1);
      fence_async_smem();
      mbar_expect(b0, 8192);
      tma2d(xs + w * 8192, &p.xm, b0, w * 64, tb * 128 + wg * 64);
      if (w < 3) {
        mbar_expect(b0 + 32, 8192);
        tma2d(xs + (w + 4) * 8192 + (warp == 6 ? 57344 : 0), &p.xm, b0 + 32, (w + 4) * 64, tb * 128 + wg * 64);
      }
    }
    TSW(2 + wg);
    asm volatile("st.shared.u32 [%0], %1;" ::"r"(sb + OFF_ONES + lane * 4), "r"(0x3f803f80) : "memory");
    fence_async_smem();
    if (warp < 4) asm volatile("barrier.cluster.wait.acquire.aligned;" ::: "memory");
  }

  if (warp < 8) {
    asm volatile("setmaxnreg.inc.sync.aligned.u32 208;");
    asm volatile("bar.sync 4, 384;" ::: "memory");
    if (wg == 1) { row_stats(sb, 1, (warp & 3) * 16 + (lane >> 1), lane); TSW(7); }
    const int g = lane >> 2, q = lane & 3;
    uint32_t a[112];
    uint32_t m0, m1;
    const uint32_t stat = sb + OFF_STAT + (warp * 16 + g) * 8;
    {
      const uint32_t xa = xs + ((warp & 3) * 16 + (lane & 15)) * 128;
      const uint64_t dOnes = mkdesc(sb + OFF_ONES, 0, 0, 0), dX = mkdesc(sb + OFF_K, 16, 1024, 1);
      float sum[4];
#pragma unroll
      for (int kt = 0; kt < 7; kt++) {
        mbar_wait(BAR(B_X + wg * 7 + kt), 0);
        const uint32_t xk = xa + kt * 8192 + ((kt == 6 && wg == 1) ? 57344 : 0);
#pragma unroll
        for (int ks = 0; ks < 4; ks++) ldsm4(&a[16 * kt + 4 * ks], xk + (((2 * ks + (lane >> 4)) ^ (lane & 7)) << 4));
        if (wg == 0) {
          wg_fence();
#pragma unroll
          for (int ks = 0; ks < 4; ks++) wgmma_ss_n8(sum, dX + (kt * 512 + ks * 2), dOnes, kt | ks);
          wg_commit();
        }
      }
      wg_wait<0>();
      reg_fence<4>(sum);
      float mu0 = sum[0] * (1.f / D_), mu1 = sum[2] * (1.f / D_);
      if (wg == 1) { mu0 = lds32f(stat); mu1 = lds32f(stat + 64); }
      m0 = pack2(mu0, mu0); m1 = pack2(mu1, mu1);
#pragma unroll
      for (int i = 0; i < 16; i++) a[i] = sub2(a[i], (i & 1) ? m1 : m0);
      asm volatile("" : "+r"(a[111]));
      if (lane < 2) mbar_arrive_cluster(mapa(BAR(B_XFREE + wg), lane));
      TSW(4 + wg);
    }
    const bool rel = (lane == 0) && ((warp & 3) < 2);
    uint32_t rel_base = mapa(bars, rank ^ (warp & 1)) + 8 * B_EMPTY;
    const uint64_t dB128 = mkdesc(sb, 8192, 1024, 1);
    const uint64_t dW = dB128 + (j & 1);
    float rs0, rs1, k0, k1;

    {
      float accK[28], accV[28];
      if (wg == 1) asm volatile("bar.sync 1, 256;" ::: "memory");
#pragma unroll
      for (int kt = 0; kt < 7; kt++) {
        mbar_wait(BAR(B_FULL + kt), 0);
        TSW(70 + 2 * kt + wg);
        wg_fence();
#pragma unroll
        for (int ks = 0; ks < 4; ks++) {
          wgmma_rs_n56(accK, &a[(kt * 4 + ks) * 4], dW + (kt * 1024 + ks * 128), kt | ks);
          wgmma_rs_n56(accV, &a[(kt * 4 + ks) * 4], dW + (kt * 1024 + 512 + ks * 128), kt | ks);
        }
        wg_commit();
        if (kt == LAG0 && wg == 0) asm volatile("bar.arrive 1, 256;" ::: "memory");
        if (kt == LAGB && wg == 1) asm volatile("bar.arrive 5, 256;" ::: "memory");
        if (kt < 6) {
#pragma unroll
          for (int i = (kt + 1) * 16; i < (kt + 2) * 16; i++) asm volatile("sub.rn.bf16x2 %0, %0, %1;" : "+r"(a[i]) : "r"((i & 1) ? m1 : m0));
        }
        if (kt > 0) { wg_wait<1>(); if (rel) mbar_arrive_cluster(rel_base + 8 * (kt - 1)); }
      }
      mbar_wait(BAR(B_XFREE), 0);
      k0 = lds32f(stat + 4); k1 = lds32f(stat + 68);
      rs0 = rcp(k0); rs1 = rcp(k1);
      k0 *= k0; k1 *= k1;
      asm volatile("" : "+f"(rs0), "+f"(rs1));
      wg_wait<0>();
      reg_fence<28>(accK); reg_fence<28>(accV);
      if (rel) mbar_arrive_cluster(rel_base + 8 * 6);
      TSW(10 + wg);
      const uint32_t ka = sb + OFF_K + (lane >> 4) * KVB + (2 + 2 * warp + ((lane >> 3) & 1)) * 896 + (lane & 7) * 16;
#pragma unroll
      for (int c = 0; c < 7; c++)
        stsm4(ka + c * 128, pack2(accK[4 * c] * rs0, accK[4 * c + 1] * rs0), pack2(accK[4 * c + 2] * rs1, accK[4 * c + 3] * rs1),
              pack2(accV[4 * c] * rs0, accV[4 * c + 1] * rs0), pack2(accV[4 * c + 2] * rs1, accV[4 * c + 3] * rs1));
      fence_async_smem();
      __syncwarp();
      if (lane == 0) mbar_arrive(BAR(B_KV));
      TSW(12 + wg);
    }
    const float c10 = -rs0 * LOG2E, c11 = -rs1 * LOG2E;
    const uint32_t tile_off = (lane >> 4) * 1024 + ((warp & 3) * 16 + (lane & 15)) * 16;
    const uint32_t hs_st = sb + OFF_HS + wg * 8192 + tile_off;
    const int bar_mine = 5 - 4 * wg, bar_other = 1 + 4 * wg;

    {
      const uint64_t dB64 = mkdesc(sb + 8192, 4096, 512, 2);
      float accQ[28], accG[32];
      asm volatile("bar.sync %0, 256;" ::"r"(bar_mine) : "memory");
#pragma unroll
      for (int kt = 0; kt < 7; kt++) {
        const int st = (7 + kt) % 10;
        mbar_wait(BAR(B_FULL + st), kt >= 3);
        if (kt == 0) TSW(14 + wg);
        wg_fence();
#pragma unroll
        for (int ks = 0; ks < 4; ks++) {
          wgmma_rs_n56(accQ, &a[(kt * 4 + ks) * 4], dW + (st * 1024 + ks * 128), kt | ks);
          wgmma_rs_n64(accG, &a[(kt * 4 + ks) * 4], dB64 + (st * 1024 + ks * 64), kt | ks);
        }
        wg_commit();
        if (kt == LAGA) asm volatile("bar.arrive %0, 256;" ::"r"(bar_other) : "memory");
        if (kt > 0) { wg_wait<1>(); if (rel) mbar_arrive_cluster(rel_base + 8 * ((6 + kt) % 10)); }
      }
      wg_wait<0>();
      reg_fence<28>(accQ); reg_fence<32>(accG);
      if (rel) mbar_arrive_cluster(rel_base + 8 * 3);
      TSW(16 + wg);
      const uint32_t qa = hs_st - (OFF_HS - OFF_Q);
      uint32_t qp[14];
#pragma unroll
      for (int c = 0; c < 7; c++) { qp[2 * c] = pack2(accQ[4 * c] * rs0, accQ[4 * c + 1] * rs0); qp[2 * c + 1] = pack2(accQ[4 * c + 2] * rs1, accQ[4 * c + 3] * rs1); }
      stsm4(qa, qp[0], qp[1], qp[2], qp[3]);
      stsm4(qa + 2048, qp[4], qp[5], q < 2 ? qp[6] : 0u, q < 2 ? qp[7] : 0u);
      stsm4(qa + 4096, q < 2 ? 0u : qp[6], q < 2 ? 0u : qp[7], qp[8], qp[9]);
      stsm4(qa + 6144, qp[10], qp[11], qp[12], qp[13]);
#pragma unroll
      for (int c = 0; c < 2; c++) {
        uint32_t hp[4];
#pragma unroll
        for (int e = 0; e < 2; e++) {
          const float* gg = &accG[8 * c + 4 * e]; const float* uu = &accG[16 + 8 * c + 4 * e];
          hp[2 * e] = swiglu2(gg[0], uu[0], gg[1], uu[1], c10, k0);
          hp[2 * e + 1] = swiglu2(gg[2], uu[2], gg[3], uu[3], c11, k1);
        }
        stsm4(hs_st + c * 2048, hp[0], hp[1], hp[2], hp[3]);
      }
      fence_async_smem();
      __syncwarp();
      if (lane < 2) mbar_arrive(BAR(B_Q + wg + 2 * lane));
      TSW(18 + wg);
    }

    Ring rg{4, 1};
#pragma unroll 1
    for (int c3 = 0; c3 < 3; c3++) {
      float acc[64];
      if (c3 == 2) rel_base = mapa(bars, rank) + 8 * B_EMPTY;
      asm volatile("bar.sync %0, 256;" ::"r"(bar_mine) : "memory");
      uint32_t prev = 0;
#pragma unroll
      for (int kt = 0; kt < 7; kt++) {
        mbar_wait(BAR(B_FULL + rg.st), rg.ph);
        if (kt == 0) TSW(20 + 6 * c3 + wg);
        const uint64_t db = dB128 + (uint64_t)(rg.st * (STAGE >> 4));
        wg_fence();
#pragma unroll
        for (int ks = 0; ks < 4; ks++) wgmma_rs_n128(acc, &a[(kt * 4 + ks) * 4], db + ks * 128, kt | ks);
        wg_commit();
        if (kt == LAGA) asm volatile("bar.arrive %0, 256;" ::"r"(bar_other) : "memory");
        if (kt > 0) { wg_wait<1>(); if (rel) mbar_arrive_cluster(rel_base + 8 * prev); }
        prev = rg.st; rg.next();
      }
      mbar_wait(BAR(B_HFREE + wg), c3 & 1);
      wg_wait<0>();
      reg_fence<64>(acc);
      if (rel) mbar_arrive_cluster(rel_base + 8 * prev);
      TSW(22 + 6 * c3 + wg);
#pragma unroll
      for (int i = 0; i < 32; i++) { acc[32 + i] *= acc[i]; acc[i] = ex2(acc[i] * ((i & 2) ? c11 : c10)); }
#pragma unroll
      for (int i = 0; i < 32; i++) { const float k = (i & 2) ? k1 : k0; acc[i] = rcp(fmaf(acc[i], k, k)); }
#pragma unroll
      for (int c = 0; c < 4; c++) {
        uint32_t hp[4];
#pragma unroll
        for (int e = 0; e < 4; e++) { const int i = 8 * c + 2 * e; hp[e] = pack2(acc[i] * acc[32 + i], acc[i + 1] * acc[33 + i]); }
        stsm4(hs_st + c * 2048, hp[0], hp[1], hp[2], hp[3]);
      }
      fence_async_smem();
      __syncwarp();
      if (lane == 0) mbar_arrive(BAR(B_H + wg));
      TSW(24 + 6 * c3 + wg);
    }

    const int ocol = qn * 112 + rank * 56;
    const uint64_t dA = mkdesc(sb, 1024, 128, 0);
    const uint64_t dBn = mkdesc(sb, 128, 1024, 0);
    const bool rel2 = (tid & 127) == 0;
    float dacc[56];
    int pr = 0, ph = 0, prev = 0;
    if (wg == 0) asm volatile("bar.sync 5, 256;" ::: "memory");
#pragma unroll 1
    for (int kt = 0; kt < 14; kt++) {
      mbar_wait(BAR(B_FULL2 + pr), ph);
      TSW(84 + 2 * kt + wg);
      const uint64_t da = dA + (uint64_t)((pr < 3 ? 5 + 2 * pr : 2 * pr - 5) * 1024 + wg * 512);
      const uint64_t db = dBn + (uint64_t)((pr < 2 ? 6 + 2 * pr : 2 * pr - 4) * 1024);
      wg_fence();
#pragma unroll
      for (int ks = 0; ks < 4; ks++) wgmma_ss_n112(dacc, da + ks * 128, db + ks * 16, kt | ks);
      wg_commit();
      wg_wait<1>();
      if (rel2 && kt > 0) mbar_arrive(BAR(B_EMPTY2 + prev));
      prev = pr;
      if (++pr == 5) { pr = 0; ph ^= 1; }
    }
    float sacc[28];
    const uint32_t part = sb + OFF_PART + warp * 1792;
    const uint64_t dO = dA + (uint64_t)(wg * 1024), dWo = dBn + (OFF_WOB >> 4);
    auto wo_step = [&](int k) {
      const uint64_t da = k < 24 ? dO + ((3 + 2 * (k >> 3)) * 1024 + (k & 7) * 128) : dA + (uint64_t)((1 - wg) * 9216) + (k & 7) * 128;
      wgmma_ss_n56(sacc, da, dWo + ((k >> 2) * 448 + (k & 3) * 16), k);
    };
    {
      mbar_wait(BAR(B_WOB), 0);
      mbar_wait(BAR(B_PFREE), 0);
      mbar_wait(BAR(B_FULL2 + 4), 0);
      TSW(112 + wg);
      const uint32_t dst = mapa(part, rank ^ 1) + lane * 16, pb = mapa(BAR(B_PART + 2 * wg), rank ^ 1);
      wg_fence();
      wo_step(0); wo_step(1);
      wg_commit();
      wg_wait<1>();
      reg_fence<56>(dacc);
      TSW(38 + wg);
      wg_fence();
#pragma unroll
      for (int i = 0; i < 4; i++) {
        const float* d = &dacc[28 + 8 * i];
        if (i < 3)
          asm volatile("st.async.shared::cluster.mbarrier::complete_tx::bytes.v4.b32 [%0], {%1,%2,%3,%4}, [%5];"
                       ::"r"(dst + i * 512), "r"(pack2(d[0], d[1])), "r"(pack2(d[2], d[3])), "r"(pack2(d[4], d[5])), "r"(pack2(d[6], d[7])), "r"(pb + (i >> 1) * 8) : "memory");
        else
          asm volatile("st.async.shared::cluster.mbarrier::complete_tx::bytes.v2.b32 [%0], {%1,%2}, [%3];"
                       ::"r"(dst + 1536 - lane * 8), "r"(pack2(d[0], d[1])), "r"(pack2(d[2], d[3])), "r"(pb + 8) : "memory");
        wo_step(2 + i);
      }
      wo_step(6); wo_step(7);
      wg_commit();
      TSW(40 + wg);
      mbar_wait(BAR(B_FULL2), 1);
      wg_fence();
#pragma unroll
      for (int k = 8; k < 16; k++) wo_step(k);
      wg_commit();
      TSW(114 + wg);
      uint32_t gp[14], xr[14];
      mbar_wait(BAR(B_FULL2 + 1), 1);
      mbar_wait(BAR(B_PART + 2 * wg), 0);
      TSW(120 + wg);
      lds128v(&gp[0], part + lane * 16); lds128v(&gp[4], part + 512 + lane * 16);
      wg_fence();
#pragma unroll
      for (int i = 0; i < 8; i++) { wo_step(16 + i); gp[i] = gate2(dacc[2 * i], dacc[2 * i + 1], gp[i]); asm volatile("" : "+r"(gp[i])); }
      wg_commit();
      TSW(116 + wg);
      mbar_wait(BAR(B_FULL2 + 2), 1);
      mbar_wait(BAR(B_PART + 2 * wg + 1), 0);
      lds128v(&gp[8], part + 1024 + lane * 16);
      asm volatile("ld.shared.v2.u32 {%0,%1}, [%2];" : "=r"(gp[12]), "=r"(gp[13]) : "r"(part + 1536 + lane * 8) : "memory");
      const uint32_t xra = sb + (wg ? 0 : 9 * STAGE) + 8192 + ((warp & 3) * 16 + (lane & 15)) * 112 + (lane >> 4) * 16;
#pragma unroll
      for (int c = 0; c < 3; c++) ldsm4(&xr[4 * c], xra + c * 32);
      asm volatile("ldmatrix.sync.aligned.m8n8.x2.shared.b16 {%0,%1}, [%2];" : "=r"(xr[12]), "=r"(xr[13]) : "r"(xra + 96) : "memory");
      wg_fence();
#pragma unroll
      for (int i = 8; i < 14; i++) { if (i < 12) wo_step(16 + i); if (i == 11) wg_commit(); gp[i] = gate2(dacc[2 * i], dacc[2 * i + 1], gp[i]); }
#pragma unroll
      for (int i = 0; i < 14; i++) asm volatile("" : "+r"(gp[i])::"memory");
      TSW(122 + wg);
      if (lane == 0) mbar_arrive(BAR(B_DONE));
      wg_wait<0>();
      reg_fence<28>(sacc);
      TSW(42 + wg);
      uint32_t yo[14];
#pragma unroll
      for (int c = 0; c < 14; c++) yo[c] = add2(xr[c], mul2(pack2(sacc[2 * c], sacc[2 * c + 1]), gp[c]));
      __syncwarp();
      const uint32_t oa = part + (lane & 15) * 112 + (lane >> 4) * 16;
#pragma unroll
      for (int c = 0; c < 3; c++) stsm4(oa + c * 32, yo[4 * c], yo[4 * c + 1], yo[4 * c + 2], yo[4 * c + 3]);
      stsm2(oa + 96, yo[12], yo[13]);
      fence_async_smem();
      __syncwarp();
      if (lane == 0) {
        asm volatile("cp.async.bulk.tensor.2d.global.shared::cta.bulk_group [%0, {%2,%3}], [%1];"
                     ::"l"(&p.outm), "r"(part), "r"(ocol), "r"(T2 * 128 + warp * 16) : "memory");
        bulk_commit();
        bulk_wait0_read();
      }
    }
    TSW(44 + wg);
  } else {
    asm volatile("setmaxnreg.dec.sync.aligned.u32 72;");
    asm volatile("bar.sync 4, 384;" ::: "memory");
    if (tid == 256) {
      mbar_wait(BAR(B_X), 0);
      asm volatile("cp.async.bulk.prefetch.L2.global [%0], %1;" ::"l"(wd + blockIdx.x * 784), "r"(12544) : "memory");
      if (blockIdx.x < 112) asm volatile("cp.async.bulk.prefetch.L2.global [%0], %1;" ::"l"(wo_in + blockIdx.x * 224), "r"(3584) : "memory");
    }
    __syncwarp();
    row_stats(sb, 0, (warp & 3) * 16 + (lane >> 1), lane);
    if (lane < 2) mbar_arrive_cluster(mapa(BAR(B_XFREE), lane));
    TSW(6);
    const int w = warp & 3, g = lane >> 2, q = lane & 3;
    {
      const int t = tid & 127, ch = t >> 1, e = (ch * 37) >> 8;
      const int r0 = blockIdx.x * 14 + (t & 1), r1 = blockIdx.x * 4 + (t & 1);
      const int d0 = ((e >> 1) * 28 * 14 + ch - e * 7 + (((e ^ (blockIdx.x >> 6)) & 1) * 7)) * 64;
      const int d1 = F_ * D_ / 8 + (e * 42 + ch) * 64 + r1 + (r1 >> 6) * 384 - 14;
      const int n = t < 112 ? (blockIdx.x < 112 ? 9 : 7) : 0;
#pragma unroll 1
      for (int i0 = 0; i0 < 9; i0 += 3) {
        uint4 v[3];
#pragma unroll
        for (int k = 0; k < 3; k++) { const int i = i0 + k; if (i < n) v[k] = ldg128((i < 7 ? wd + r0 * 56 : wo_in + (r1 - 14) * 56) + (i * 112 + ch)); }
#pragma unroll
        for (int k = 0; k < 3; k++) { const int i = i0 + k, row = r0 + 2 * i; if (i < n) gs->wd[i < 7 ? d0 + row + (row >> 6) * 832 : d1 + 2 * i] = v[k]; }
      }
      asm volatile("bar.sync 2, 128;" ::: "memory");
      if (tid == 256) { flag_add_rel(&gs->flag[F_W * 8]); TS(67); }
    }
    const int par = g & 1;
    const float sl2 = 0.1889822365046136f * LOG2E;
    uint32_t o3a = 0, o3b = 0;
    mbar_wait(BAR(B_KV), 0);
    mbar_wait(BAR(B_HALO), 0);
    if (rank == 1 && tid == 256) mbar_arrive_cluster(mapa(BAR(B_KVFREE), 0));
#pragma unroll 1
    for (int it = 0; it < 4; it++) {
      const int mt = it >> 1, hh = it & 1;
      mbar_wait(BAR(B_Q + mt), 0);
      if (hh == 0) TSW(46 + 2 * mt);
      const uint64_t dQ = mkdesc(sb + OFF_Q, 1024, 128, 0) + (uint64_t)(mt * 512 + hh * 256);
      const uint64_t dK = mkdesc(sb + OFF_K, 128, 896, 0) + (uint64_t)(mt * 448 + hh * 24);
      const uint64_t dV = mkdesc(sb + OFF_V, 896, 128, 0) + (uint64_t)(mt * 448 + hh * 24);
      const int jmin = 16 - (tb * 128 + mt * 64 + w * 16);
      float s[40];
      wg_fence();
      wgmma_ssk_n80(s, dQ, dK, 0);
      wgmma_ssk_n80(s, dQ + 128, dK + 16, 1);
      wg_commit();
      wg_wait<0>();
      reg_fence<40>(s);
      float u[20], v[12], l[8];
#pragma unroll
      for (int i = 0; i < 20; i++) u[i] = par ? s[2 * i + 1] : s[2 * i];
#pragma unroll
      for (int i = 0; i < 12; i++) v[i] = (w & 2) ? u[i + 8] : u[i];
      float m0 = -INFINITY, m1 = -INFINITY;
#pragma unroll
      for (int n = 0; n < 4; n++) {
        const int jj = 8 * n + 2 * q + par;
        const uint32_t d0 = g + 16 - jj, d1 = d0 + 8;
        l[2 * n] = (n < 3 && jj >= jmin && d0 <= 14) ? ((w & 1) ? v[2 * n + 4] : v[2 * n]) : -INFINITY;
        l[2 * n + 1] = (n > 0 && jj >= jmin && d1 <= 14) ? ((w & 1) ? v[2 * n + 5] : v[2 * n + 1]) : -INFINITY;
        m0 = fmaxf(m0, l[2 * n]); m1 = fmaxf(m1, l[2 * n + 1]);
      }
      m0 = fmaxf(m0, __shfl_xor_sync(~0u, m0, 1)); m1 = fmaxf(m1, __shfl_xor_sync(~0u, m1, 1));
      m0 = fmaxf(m0, __shfl_xor_sync(~0u, m0, 2)); m1 = fmaxf(m1, __shfl_xor_sync(~0u, m1, 2));
      float z0 = 0.f, z1 = 0.f;
#pragma unroll
      for (int n = 0; n < 4; n++) {
        l[2 * n] = n < 3 ? ex2((l[2 * n] - m0) * sl2) : 0.f; l[2 * n + 1] = n > 0 ? ex2((l[2 * n + 1] - m1) * sl2) : 0.f;
        z0 += l[2 * n]; z1 += l[2 * n + 1];
      }
      z0 += __shfl_xor_sync(~0u, z0, 1); z1 += __shfl_xor_sync(~0u, z1, 1);
      z0 += __shfl_xor_sync(~0u, z0, 2); z1 += __shfl_xor_sync(~0u, z1, 2);
      const float i0 = rcp(z0), i1 = rcp(z1);
      uint32_t pf[8];
#pragma unroll
      for (int i = 0; i < 8; i++) pf[i] = (i == 1 || i == 6) ? 0u : pack2(l[i] * ((i & 1) ? i1 : i0), 0.f) << (16 * par);
      uint32_t pa[5][4];
#pragma unroll
      for (int k = 0; k < 5; k++)
#pragma unroll
        for (int r = 0; r < 4; r++) pa[k][r] = (k < 4 && k == w) ? pf[r] : ((k > 0 && k == w + 1) ? pf[4 + r] : 0u);
      float o[16];
      wg_fence();
#pragma unroll
      for (int k = 0; k < 5; k++) wgmma_rs_n32(o, pa[k], dV + k * 112, k);
      wg_commit();
      wg_wait<0>();
      reg_fence<16>(o);
      const uint32_t qa = sb + OFF_Q + mt * 8192 + hh * 3072 + (lane >> 4) * 1024 + (w * 16 + (lane & 15)) * 16;
      const bool keep = hh && q < 2;
      stsm4(qa, keep ? o3a : pack2(o[0], o[1]), keep ? o3b : pack2(o[2], o[3]), pack2(o[4], o[5]), pack2(o[6], o[7]));
      o3a = pack2(o[12], o[13]); o3b = pack2(o[14], o[15]);
      stsm4(qa + 2048, pack2(o[8], o[9]), pack2(o[10], o[11]), o3a, o3b);
      if (hh) {
        fence_async_smem();
        asm volatile("bar.sync 2, 128;" ::: "memory");
        if (tid == 256) {
          bulk_s2g(gs->o + ((tb * 2 + mt) * 56 + 7 * j) * 64, sb + OFF_Q + mt * 8192, 7168);
          bulk_commit();
        }
        TSW(47 + 2 * mt);
      }
    }
    if (tid == 256) {
      bulk_wait0();
      TS(50);
      flag_add(&gs->flag[(F_O + tb) * 8]);
      const uint4* wo = gs->wo + (2 * qn + rank) * 3136;
      mbar_wait(BAR(B_WOK), 0);
      mbar_wait(BAR(B_KVFREE), 0);
      mbar_expect(BAR(B_WOB), 50176);
      bulk_g2s(sb + OFF_WOB, wo, 43008, BAR(B_WOB));
      mbar_wait(BAR(B_HLAST), 0);
      bulk_g2s(sb + OFF_WOB + 43008, wo + 2688, 7168, BAR(B_WOB));
      mbar_arrive(BAR(B_DONE));
    }
  }
  } else {
    asm volatile("setmaxnreg.dec.sync.aligned.u32 24;");
    if (lane == 0) {
      if (warp == 12) {
        prefetch_map(&p.wqkv);
#pragma unroll
        for (int i = 0; i < B_PART; i++) mbar_init(BAR(i), 1);
        mbar_init(BAR(B_KV), 8); mbar_init(BAR(B_XFREE), 16); mbar_init(BAR(B_XFREE + 1), 8); mbar_init(BAR(B_DONE), 12);
      } else if (warp == 13) {
#pragma unroll
        for (int i = B_PART; i < B_X; i++) mbar_init(BAR(i), 1);
#pragma unroll
        for (int i = 0; i < 4; i++) mbar_expect(BAR(B_PART + i), 4096 - (i & 1) * 1024);
        if (rank) mbar_expect(BAR(B_HALO), 3584);
      } else if (warp == 14) {
#pragma unroll
        for (int i = B_ORDY; i < B_EMPTY; i++) mbar_init(BAR(i), i < B_FULL2 ? 1 : 2);
      } else {
#pragma unroll
        for (int i = B_EMPTY; i < B_KV; i++) mbar_init(BAR(i), 4);
      }
      asm volatile("fence.mbarrier_init.release.cluster;" ::: "memory");
    }
    __syncwarp();
    asm volatile("barrier.cluster.arrive.relaxed.aligned;" ::: "memory");
    asm volatile("barrier.cluster.wait.acquire.aligned;" ::: "memory");
    if (warp == 13) {
      const uint32_t epoch = *(volatile uint32_t*)&gs->flag[(F_EPOCH + blockIdx.x) * 8] + 1;
      if (rank == 0) {
        mbar_wait_lim(BAR(B_KV), 0);
        if (tb == 0) {
#pragma unroll 1
          for (int c = lane; c < 224; c += 32) sts128(sb + (c < 112 ? OFF_K : OFF_V - 1792) + c * 16, make_uint4(0, 0, 0, 0));
          fence_async_smem();
          __syncwarp();
          if (lane == 0) mbar_arrive(BAR(B_HALO));
        } else {
          const uint32_t* f = &gs->flag[(F_HALO + (tb - 1) * 8 + j) * 8];
          int it = 0;
          while ((int32_t)(ld_flag(f) - epoch) < 0) { if (++it > (1 << 20)) __trap(); }
          fence_async_global();
          if (lane == 0) mbar_expect(BAR(B_HALO), 3584);
          __syncwarp();
          if (lane < 2) bulk_g2s(sb + OFF_K + lane * KVB, gs->halo + ((tb - 1) * 8 + j) * 224 + lane * 112, 1792, BAR(B_HALO));
          if (lane == 0) TS(55);
        }
      }
      const int box = lane < 2 ? 12 + lane : lane - 2;
      const uint32_t* flag = &gs->flag[(lane < 14 ? F_H + (T2 * 2 + rank) * 14 + box : (lane == 14 ? F_O + T2 : F_W)) * 8];
      const uint32_t target = epoch * (lane < 2 ? 4 : (lane < 14 ? 2 : (lane == 14 ? 8 : 128)));
      mbar_wait_lim(BAR(B_GO), 0);
      bool pend = lane < 16;
      int it = 0;
      while (true) {
        if (pend && (int32_t)(ld_flag(flag) - target) >= 0) {
          fence_async_global();
          mbar_arrive(BAR(B_X + lane));
          pend = false;
          if (lane == 10) TS(57);
          if (lane == 13) TS(58);
        }
        if (!__any_sync(~0u, pend)) break;
        if (++it > (1 << 20)) __trap();
      }
      if (lane == 0) gs->flag[(F_EPOCH + blockIdx.x) * 8] = epoch;
      mbar_wait_lim(BAR(B_DONE), 0);
    } else if (lane == 0) {
      if (warp == 14) {
        mbar_wait(BAR(B_KV), 0);
        if (rank == 0) {
          const uint32_t hb = mapa(BAR(B_HALO), 1);
          bulk_s2s(mapa(sb + OFF_K, 1), sb + OFF_K + 16 * 896, 1792, hb);
          bulk_s2s(mapa(sb + OFF_V, 1), sb + OFF_V + 16 * 896, 1792, hb);
        } else {
          uint4* dst = gs->halo + (tb * 8 + j) * 224;
          bulk_s2g(dst, sb + OFF_K + 16 * 896, 1792);
          bulk_s2g(dst + 112, sb + OFF_V + 16 * 896, 1792);
          bulk_commit();
          bulk_wait0();
          flag_add(&gs->flag[(F_HALO + tb * 8 + j) * 8]);
          TS(60);
          mbar_arrive(BAR(B_KVFREE));
        }
        const int hb = (tb * 2 + (j >> 2)) * 14;
#pragma unroll 1
        for (int i = 0; i < 8; i++) {
          const int ps = i >> 1, w = i & 1;
          const int box = hb + (ps == 0 ? 12 + (qn >> 1) : 4 * (ps - 1) + qn);
          mbar_wait(BAR(B_H + w), ps & 1);
          bulk_s2g(gs->h + box * 1024 + w * 512 + (ps == 0 ? (qn & 1) * 256 : 0), sb + OFF_HS + w * 8192, ps == 0 ? 4096 : 8192);
          bulk_commit();
          bulk_wait0();
          flag_add(&gs->flag[(F_H + box) * 8]);
          mbar_arrive(BAR(i == 6 ? B_HLAST : B_HFREE + w));
          if (ps >= 2) TS(63 + 2 * (ps - 2) + w);
        }
        mbar_arrive_cluster(mapa(BAR(B_PFREE), rank ^ 1));
      } else {
        const int isB = warp == 12;
        if (isB) {
          TS(52);
          prefetch_map(&p.wg32); prefetch_map(&p.wu32); prefetch_map(rank ? &p.wu : &p.wg); prefetch_map(&p.outm); prefetch_map(&p.xr);
          Ring rg{0, 1};
          const int fbase = (j >> 2) * 896;
          const int cq = j * 56 - (j & 1) * 8;
          int i = 0;
#pragma unroll 1
          for (int ps = 0; ps < 5; ps++) {
            const bool two = ps == 1 && rank == 1;
            const CUtensorMap* m = two ? &p.wg32 : (ps < 2 ? &p.wqkv : (rank ? &p.wu : &p.wg));
            const int c0 = two ? fbase + 768 + qn * 32 : (ps == 0 ? cq + D_ + D_ * rank : (ps == 1 ? cq : fbase + (4 * (ps - 2) + qn) * 64));
            if (ps == 1) mbar_wait(BAR(B_XFREE + 1), 0);
#pragma unroll 1
            for (int kt = 0; kt < 7; kt++, i++) {
              mbar_wait(BAR(B_EMPTY + rg.st), rg.ph);
              const uint32_t fb = BAR(B_FULL + rg.st), dst = sb + rg.st * STAGE + rank * 8192;
              mbar_expect(fb, STAGE);
              tma2d_mc(dst, m, fb, c0, kt * 64);
              if (two) tma2d_mc(dst + 4096, &p.wu32, fb, c0, kt * 64);
              rg.next();
              if (i == 35 - NST) mbar_arrive(BAR(B_GO));
            }
          }
          TS(53);
        }
        mbar_wait(BAR(isB ? B_WOK : B_GO), 0);
        const int tile = isB ? 896 : 1024;
        const uint4* src = isB ? gs->wd + (qn * 28 + rank * 14) * 896 : gs->h + (T2 * 2 + rank) * 14 * 1024;
        const uint4* osrc = gs->o + (T2 * 2 + isB) * 56 * 64;
        int pr = 0;
#pragma unroll 1
        for (int kt = 0; kt < 18; kt++) {
          int sl = 5 + isB + 2 * pr;
          if (sl >= 10) sl -= 10;
          if (kt == 14 || (kt < 14 && !isB)) mbar_wait(BAR(B_X + kt), kt < 14);
          mbar_wait(BAR(kt < 5 ? B_EMPTY + sl : B_EMPTY2 + pr), kt < 5 ? sl < 5 : (kt >= 10 && kt < 15));
          const int bytes = kt < 14 ? tile * 16 : (kt < 17 ? STAGE : 8192);
          mbar_expect(BAR(B_FULL2 + pr), kt < 17 ? bytes : 8192 + 7168);
          if (kt == 17) tma2d(sb + sl * STAGE + 8192, &p.xr, BAR(B_FULL2 + pr), qn * 112 + rank * 56, T2 * 128 + isB * 64);
          bulk_g2s(sb + sl * STAGE, kt < 14 ? src + (kt < 2 ? 12 + kt : kt - 2) * tile : osrc + (kt - 14) * 1024, bytes, BAR(B_FULL2 + pr));
          if (!isB) { if (kt == 0) TS(56); if (kt == 10) TS(61); if (kt == 13) TS(62); if (kt == 17) TS(59); }
          if (++pr == 5) pr = 0;
        }
      }
      mbar_arrive(BAR(B_DONE));
    }
  }
#undef BAR
}

typedef CUresult (*EncFn)(CUtensorMap*, CUtensorMapDataType, cuuint32_t, void*, const cuuint64_t*, const cuuint64_t*,
                          const cuuint32_t*, const cuuint32_t*, CUtensorMapInterleave, CUtensorMapSwizzle,
                          CUtensorMapL2promotion, CUtensorMapFloatOOBfill);

void enc2d(EncFn enc, CUtensorMap* m, const void* ptr, int cols, int rows, int bc, int br, CUtensorMapSwizzle sw) {
  cuuint64_t gd[2] = {(cuuint64_t)cols, (cuuint64_t)rows};
  cuuint64_t gs[1] = {(cuuint64_t)cols * 2};
  cuuint32_t bd[2] = {(cuuint32_t)bc, (cuuint32_t)br}, es[2] = {1, 1};
  enc(m, CU_TENSOR_MAP_DATA_TYPE_BFLOAT16, 2, const_cast<void*>(ptr), gd, gs, bd, es, CU_TENSOR_MAP_INTERLEAVE_NONE, sw,
      CU_TENSOR_MAP_L2_PROMOTION_L2_128B, CU_TENSOR_MAP_FLOAT_OOB_FILL_NONE);
}

}

extern "C" void kernel_launch(void* const* d_in, const int* in_sizes, int n_in, void* d_out, int out_size) {
  static EncFn enc = nullptr;
  static Scratch* gs = nullptr;
  if (!enc) {
    cudaGetSymbolAddress((void**)&gs, g_s);
    void* fn = nullptr;
    cudaDriverEntryPointQueryResult qr;
    cudaGetDriverEntryPoint("cuTensorMapEncodeTiled", &fn, cudaEnableDefault, &qr);
    enc = (EncFn)fn;
    cudaFuncSetAttribute(fused_kernel, cudaFuncAttributeMaxDynamicSharedMemorySize, SMEM_BYTES);
  }
  Params p;
  enc2d(enc, &p.xm, d_in[0], D_, S_, 64, 64, CU_TENSOR_MAP_SWIZZLE_128B);
  enc2d(enc, &p.wqkv, d_in[1], 3 * D_, D_, 64, 64, CU_TENSOR_MAP_SWIZZLE_128B);
  enc2d(enc, &p.wg, d_in[4], F_, D_, 64, 64, CU_TENSOR_MAP_SWIZZLE_128B);
  enc2d(enc, &p.wu, d_in[5], F_, D_, 64, 64, CU_TENSOR_MAP_SWIZZLE_128B);
  enc2d(enc, &p.wg32, d_in[4], F_, D_, 32, 64, CU_TENSOR_MAP_SWIZZLE_64B);
  enc2d(enc, &p.wu32, d_in[5], F_, D_, 32, 64, CU_TENSOR_MAP_SWIZZLE_64B);
  enc2d(enc, &p.outm, d_out, D_, S_, 56, 16, CU_TENSOR_MAP_SWIZZLE_NONE);
  enc2d(enc, &p.xr, d_in[0], D_, S_, 56, 64, CU_TENSOR_MAP_SWIZZLE_NONE);
  fused_kernel<<<128, 512, SMEM_BYTES>>>(gs, (const uint4*)d_in[6], (const uint4*)d_in[2], p);
}
```

```cpp
#include <cuda_runtime.h>
#include <cuda_bf16.h>
#include <cuda.h>
#include <stdint.h>
#include <stddef.h>

namespace {

constexpr int S_ = 2048, D_ = 448, F_ = 1792;
constexpr int NST = 10;
constexpr int STAGE = 16384;
constexpr int KVB = 18 * 896;
constexpr int OFF_K = NST * STAGE;
constexpr int OFF_V = OFF_K + KVB;
constexpr int OFF_Q = OFF_V + KVB;
constexpr int OFF_HS = OFF_K + 50176;
constexpr int OFF_WOB = OFF_K;
constexpr int OFF_PART = OFF_HS;
constexpr int OFF_BAR = OFF_HS + 16384;
constexpr int SMEM_BYTES = OFF_BAR + 1024;
constexpr int B_FULL = 0, B_HFREE = 10  , B_PART = 12  , B_HALO = 16, B_GO = 17, B_PFREE = 18,
              B_X = 19  , B_ORDY = 33  , B_WOK = 35, B_KVFREE = 36, B_WOB = 37, B_STG = 38,
              B_FULL2 = 39  , B_EMPTY2 = 44  ,
              B_EMPTY = 49, B_Q = 59  , B_H = 61  ,
              B_KV = 63, B_XFREE = 64  , B_DONE = 66, B_RT = 67;
#define LEAD 12
#define LAG0 6
#define LAGP4 4
#define PD1 300
#define PD2 300
#define PSTEP 2
#define PMASK 0x9600
#define PFIRST (warp < 12)
#define LAGA 6
#define LAGB 6

struct Params {
  CUtensorMap xm, wqkv, wg, wu, wg32, wu32, wdm, wom, xr;
};

struct Scratch {
  uint4 h[S_ * F_ / 8];
  uint4 o[S_ * D_ / 8];
  uint4 wd[F_ * D_ / 8];
  uint4 wo[D_ * D_ / 8];
  uint4 halo[16 * 8 * 224];
  uint32_t flag[(448 + 32 + 1 + 128 + 128) * 8];
};
constexpr int F_H = 0, F_O = 448, F_W = 480, F_HALO = 481, F_EPOCH = 609;
__device__ Scratch g_s;
#define TS(slot)
#define TG(slot)
#define TSW(slot)
#define FIN return

#define SW(b, ph) mbar_wait(b, ph)
#define SDUMP(slot)
__device__ __forceinline__ uint32_t s2u(const void* p) { return (uint32_t)__cvta_generic_to_shared(p); }
__device__ __forceinline__ void mbar_init(uint32_t b, int c) { asm volatile("mbarrier.init.shared::cta.b64 [%0], %1;" ::"r"(b), "r"(c) : "memory"); }
__device__ __forceinline__ void mbar_expect(uint32_t b, int bytes) { asm volatile("mbarrier.arrive.expect_tx.shared::cta.b64 _, [%0], %1;" ::"r"(b), "r"(bytes) : "memory"); }
__device__ __forceinline__ void mbar_arrive(uint32_t b) { asm volatile("mbarrier.arrive.shared::cta.b64 _, [%0];" ::"r"(b) : "memory"); }
__device__ __forceinline__ void mbar_arrive_cluster(uint32_t b) { asm volatile("mbarrier.arrive.shared::cluster.b64 _, [%0];" ::"r"(b) : "memory"); }
__device__ __forceinline__ uint32_t mapa(uint32_t a, uint32_t r) { uint32_t o; asm volatile("mapa.shared::cluster.u32 %0, %1, %2;" : "=r"(o) : "r"(a), "r"(r)); return o; }
__device__ __forceinline__ void mbar_wait(uint32_t b, uint32_t ph) {
  asm volatile("{\n.reg .pred p;\nW: mbarrier.try_wait.parity.shared::cta.b64 p, [%0], %1;\n@!p bra W;\n}" ::"r"(b), "r"(ph) : "memory");
}
__device__ __forceinline__ void mbar_wait_lim(uint32_t b, uint32_t ph) {
  uint32_t ok;
  int it = 0;
  do {
    if (++it > (1 << 18)) __trap();
    asm volatile("{.reg .pred p; mbarrier.try_wait.parity.shared::cta.b64 p, [%1], %2; selp.u32 %0,1,0,p;}" : "=r"(ok) : "r"(b), "r"(ph) : "memory");
  } while (!ok);
}
__device__ __forceinline__ uint32_t ld_flag(const uint32_t* f) { uint32_t v; asm volatile("ld.relaxed.gpu.global.u32 %0, [%1];" : "=r"(v) : "l"(f) : "memory"); return v; }
__device__ __forceinline__ void flag_add(uint32_t* f) { asm volatile("red.relaxed.gpu.global.add.u32 [%0], 1;" ::"l"(f) : "memory"); }
__device__ __forceinline__ void fence_async_smem() { asm volatile("fence.proxy.async.shared::cta;" ::: "memory"); }
__device__ __forceinline__ void fence_async_global() { asm volatile("fence.proxy.async.global;" ::: "memory"); }

__device__ __forceinline__ void tma2d(uint32_t dst, const CUtensorMap* m, uint32_t bar, int c0, int c1) {
  asm volatile("cp.async.bulk.tensor.2d.shared::cluster.global.mbarrier::complete_tx::bytes [%0], [%1, {%3,%4}], [%2];" ::"r"(dst), "l"(m), "r"(bar), "r"(c0), "r"(c1) : "memory");
}
__device__ __forceinline__ void tma2d_mc(uint32_t dst, const CUtensorMap* m, uint32_t bar, int c0, int c1) {
  asm volatile("cp.async.bulk.tensor.2d.shared::cluster.global.mbarrier::complete_tx::bytes.multicast::cluster [%0], [%1, {%3,%4}], [%2], %5;" ::"r"(dst), "l"(m), "r"(bar), "r"(c0), "r"(c1), "h"((uint16_t)3) : "memory");
}
__device__ __forceinline__ void bulk_g2s(uint32_t dst, const void* src, int bytes, uint32_t bar) {
  asm volatile("cp.async.bulk.shared::cluster.global.mbarrier::complete_tx::bytes [%0], [%1], %2, [%3];" ::"r"(dst), "l"(src), "r"(bytes), "r"(bar) : "memory");
}
__device__ __forceinline__ void bulk_s2g(void* dst, uint32_t src, int bytes) {
  asm volatile("cp.async.bulk.global.shared::cta.bulk_group [%0], [%1], %2;" ::"l"(dst), "r"(src), "r"(bytes) : "memory");
}
__device__ __forceinline__ void bulk_s2s(uint32_t dst, uint32_t src, int bytes, uint32_t bar) {
  asm volatile("cp.async.bulk.shared::cluster.shared::cta.mbarrier::complete_tx::bytes [%0], [%1], %2, [%3];" ::"r"(dst), "r"(src), "r"(bytes), "r"(bar) : "memory");
}
__device__ __forceinline__ void bulk_commit() { asm volatile("cp.async.bulk.commit_group;" ::: "memory"); }
__device__ __forceinline__ void bulk_wait0() { asm volatile("cp.async.bulk.wait_group 0;" ::: "memory"); }
__device__ __forceinline__ void l2_prefetch(const void* p, int bytes) { asm volatile("cp.async.bulk.prefetch.L2.global [%0], %1;" ::"l"(p), "r"(bytes) : "memory"); }
__device__ __forceinline__ void delay(uint32_t cycles) {
  uint32_t c0, c1;
  asm volatile("mov.u32 %0, %%clock;" : "=r"(c0));
  do { asm volatile("mov.u32 %0, %%clock;" : "=r"(c1)); } while (c1 - c0 < cycles);
}
__device__ __forceinline__ void prefetch_map(const CUtensorMap* m) { asm volatile("prefetch.tensormap [%0];" ::"l"(m) : "memory"); }

__device__ __forceinline__ void ldsm4(uint32_t* r, uint32_t a) { asm volatile("ldmatrix.sync.aligned.m8n8.x4.shared.b16 {%0,%1,%2,%3}, [%4];" : "=r"(r[0]), "=r"(r[1]), "=r"(r[2]), "=r"(r[3]) : "r"(a) : "memory"); }
__device__ __forceinline__ void stsm4(uint32_t a, uint32_t r0, uint32_t r1, uint32_t r2, uint32_t r3) { asm volatile("stmatrix.sync.aligned.m8n8.x4.shared.b16 [%0], {%1,%2,%3,%4};" ::"r"(a), "r"(r0), "r"(r1), "r"(r2), "r"(r3) : "memory"); }
__device__ __forceinline__ void stsm2(uint32_t a, uint32_t r0, uint32_t r1) { asm volatile("stmatrix.sync.aligned.m8n8.x2.shared.b16 [%0], {%1,%2};" ::"r"(a), "r"(r0), "r"(r1) : "memory"); }
__device__ __forceinline__ uint32_t pack2(float lo, float hi) { uint32_t r; asm("cvt.rn.bf16x2.f32 %0, %1, %2;" : "=r"(r) : "f"(hi), "f"(lo)); return r; }
__device__ __forceinline__ float bf_lo(uint32_t v) { return __uint_as_float(v << 16); }
__device__ __forceinline__ float bf_hi(uint32_t v) { return __uint_as_float(v & 0xffff0000u); }
__device__ __forceinline__ float rbf(float v) { return bf_lo(pack2(v, 0.f)); }
__device__ __forceinline__ uint32_t sub2(uint32_t a, uint32_t b) { uint32_t r; asm("sub.rn.bf16x2 %0, %1, %2;" : "=r"(r) : "r"(a), "r"(b)); return r; }
__device__ __forceinline__ uint32_t add2(uint32_t a, uint32_t b) { uint32_t r; asm("add.rn.bf16x2 %0, %1, %2;" : "=r"(r) : "r"(a), "r"(b)); return r; }
__device__ __forceinline__ uint32_t mul2(uint32_t a, uint32_t b) { uint32_t r; asm("mul.rn.bf16x2 %0, %1, %2;" : "=r"(r) : "r"(a), "r"(b)); return r; }
__device__ __forceinline__ float ex2(float v) { float r; asm("ex2.approx.ftz.f32 %0, %1;" : "=f"(r) : "f"(v)); return r; }
__device__ __forceinline__ float tanh_approx(float v) { float r; asm("tanh.approx.f32 %0, %1;" : "=f"(r) : "f"(v)); return r; }
__device__ __forceinline__ float sqrt_approx(float v) { float r; asm("sqrt.approx.ftz.f32 %0, %1;" : "=f"(r) : "f"(v)); return r; }
__device__ __forceinline__ float rcp(float v) { float r; asm("rcp.approx.ftz.f32 %0, %1;" : "=f"(r) : "f"(v)); return r; }
__device__ __forceinline__ void lds128v(uint32_t* v, uint32_t a) { asm volatile("ld.shared.v4.u32 {%0,%1,%2,%3}, [%4];" : "=r"(v[0]), "=r"(v[1]), "=r"(v[2]), "=r"(v[3]) : "r"(a) : "memory"); }
__device__ __forceinline__ void sts128(uint32_t a, uint4 v) { asm volatile("st.shared.v4.u32 [%0], {%1,%2,%3,%4};" ::"r"(a), "r"(v.x), "r"(v.y), "r"(v.z), "r"(v.w) : "memory"); }

__device__ __forceinline__ void wg_fence() { asm volatile("wgmma.fence.sync.aligned;" ::: "memory"); }
__device__ __forceinline__ void wg_commit() { asm volatile("wgmma.commit_group.sync.aligned;" ::: "memory"); }
template <int N> __device__ __forceinline__ void wg_wait() { asm volatile("wgmma.wait_group.sync.aligned %0;" ::"n"(N) : "memory"); }
template <int N> __device__ __forceinline__ void reg_fence(float* d) {
#pragma unroll
  for (int i = 0; i < N; i++) asm volatile("" : "+f"(d[i])::"memory");
}
template <int N> __device__ __forceinline__ void zero(float* d) {
#pragma unroll
  for (int i = 0; i < N; i++) d[i] = 0.f;
}
__device__ __forceinline__ uint64_t mkdesc(uint32_t addr, uint32_t lbo, uint32_t sbo, uint32_t sw) {
  return (uint64_t)((addr & 0x3FFFF) >> 4) | ((uint64_t)(lbo >> 4) << 16) | ((uint64_t)(sbo >> 4) << 32) | ((uint64_t)sw << 62);
}

__device__ __forceinline__ void wgmma_rs_n56(float* d, const uint32_t* a, uint64_t db, int sd) {
  asm volatile("{\n.reg .pred p;\nsetp.ne.b32 p, %33, 0;\nwgmma.mma_async.sync.aligned.m64n56k16.f32.bf16.bf16 {%0,%1,%2,%3,%4,%5,%6,%7,%8,%9,%10,%11,%12,%13,%14,%15,%16,%17,%18,%19,%20,%21,%22,%23,%24,%25,%26,%27}, {%28,%29,%30,%31}, %32, p, 1, 1, 1;\n}\n"
    : "+f"(d[0]),"+f"(d[1]),"+f"(d[2]),"+f"(d[3]),"+f"(d[4]),"+f"(d[5]),"+f"(d[6]),"+f"(d[7]),"+f"(d[8]),"+f"(d[9]),"+f"(d[10]),"+f"(d[11]),"+f"(d[12]),"+f"(d[13]),"+f"(d[14]),"+f"(d[15]),"+f"(d[16]),"+f"(d[17]),"+f"(d[18]),"+f"(d[19]),"+f"(d[20]),"+f"(d[21]),"+f"(d[22]),"+f"(d[23]),"+f"(d[24]),"+f"(d[25]),"+f"(d[26]),"+f"(d[27])
    : "r"(a[0]),"r"(a[1]),"r"(a[2]),"r"(a[3]),"l"(db),"r"(sd));
}
__device__ __forceinline__ void wgmma_rs_n64(float* d, const uint32_t* a, uint64_t db, int sd) {
  asm volatile("{\n.reg .pred p;\nsetp.ne.b32 p, %37, 0;\nwgmma.mma_async.sync.aligned.m64n64k16.f32.bf16.bf16 {%0,%1,%2,%3,%4,%5,%6,%7,%8,%9,%10,%11,%12,%13,%14,%15,%16,%17,%18,%19,%20,%21,%22,%23,%24,%25,%26,%27,%28,%29,%30,%31}, {%32,%33,%34,%35}, %36, p, 1, 1, 1;\n}\n"
    : "+f"(d[0]),"+f"(d[1]),"+f"(d[2]),"+f"(d[3]),"+f"(d[4]),"+f"(d[5]),"+f"(d[6]),"+f"(d[7]),"+f"(d[8]),"+f"(d[9]),"+f"(d[10]),"+f"(d[11]),"+f"(d[12]),"+f"(d[13]),"+f"(d[14]),"+f"(d[15]),"+f"(d[16]),"+f"(d[17]),"+f"(d[18]),"+f"(d[19]),"+f"(d[20]),"+f"(d[21]),"+f"(d[22]),"+f"(d[23]),"+f"(d[24]),"+f"(d[25]),"+f"(d[26]),"+f"(d[27]),"+f"(d[28]),"+f"(d[29]),"+f"(d[30]),"+f"(d[31])
    : "r"(a[0]),"r"(a[1]),"r"(a[2]),"r"(a[3]),"l"(db),"r"(sd));
}
__device__ __forceinline__ void wgmma_rs_n128(float* d, const uint32_t* a, uint64_t db, int sd) {
  asm volatile("{\n.reg .pred p;\nsetp.ne.b32 p, %69, 0;\nwgmma.mma_async.sync.aligned.m64n128k16.f32.bf16.bf16 {%0,%1,%2,%3,%4,%5,%6,%7,%8,%9,%10,%11,%12,%13,%14,%15,%16,%17,%18,%19,%20,%21,%22,%23,%24,%25,%26,%27,%28,%29,%30,%31,%32,%33,%34,%35,%36,%37,%38,%39,%40,%41,%42,%43,%44,%45,%46,%47,%48,%49,%50,%51,%52,%53,%54,%55,%56,%57,%58,%59,%60,%61,%62,%63}, {%64,%65,%66,%67}, %68, p, 1, 1, 1;\n}\n"
    : "+f"(d[0]),"+f"(d[1]),"+f"(d[2]),"+f"(d[3]),"+f"(d[4]),"+f"(d[5]),"+f"(d[6]),"+f"(d[7]),"+f"(d[8]),"+f"(d[9]),"+f"(d[10]),"+f"(d[11]),"+f"(d[12]),"+f"(d[13]),"+f"(d[14]),"+f"(d[15]),"+f"(d[16]),"+f"(d[17]),"+f"(d[18]),"+f"(d[19]),"+f"(d[20]),"+f"(d[21]),"+f"(d[22]),"+f"(d[23]),"+f"(d[24]),"+f"(d[25]),"+f"(d[26]),"+f"(d[27]),"+f"(d[28]),"+f"(d[29]),"+f"(d[30]),"+f"(d[31]),"+f"(d[32]),"+f"(d[33]),"+f"(d[34]),"+f"(d[35]),"+f"(d[36]),"+f"(d[37]),"+f"(d[38]),"+f"(d[39]),"+f"(d[40]),"+f"(d[41]),"+f"(d[42]),"+f"(d[43]),"+f"(d[44]),"+f"(d[45]),"+f"(d[46]),"+f"(d[47]),"+f"(d[48]),"+f"(d[49]),"+f"(d[50]),"+f"(d[51]),"+f"(d[52]),"+f"(d[53]),"+f"(d[54]),"+f"(d[55]),"+f"(d[56]),"+f"(d[57]),"+f"(d[58]),"+f"(d[59]),"+f"(d[60]),"+f"(d[61]),"+f"(d[62]),"+f"(d[63])
    : "r"(a[0]),"r"(a[1]),"r"(a[2]),"r"(a[3]),"l"(db),"r"(sd));
}
__device__ __forceinline__ void wgmma_ss_n112(float* d, uint64_t da, uint64_t db, int sd) {
  asm volatile("{\n.reg .pred p;\nsetp.ne.b32 p, %58, 0;\nwgmma.mma_async.sync.aligned.m64n112k16.f32.bf16.bf16 {%0,%1,%2,%3,%4,%5,%6,%7,%8,%9,%10,%11,%12,%13,%14,%15,%16,%17,%18,%19,%20,%21,%22,%23,%24,%25,%26,%27,%28,%29,%30,%31,%32,%33,%34,%35,%36,%37,%38,%39,%40,%41,%42,%43,%44,%45,%46,%47,%48,%49,%50,%51,%52,%53,%54,%55}, %56, %57, p, 1, 1, 0, 1;\n}\n"
    : "+f"(d[0]),"+f"(d[1]),"+f"(d[2]),"+f"(d[3]),"+f"(d[4]),"+f"(d[5]),"+f"(d[6]),"+f"(d[7]),"+f"(d[8]),"+f"(d[9]),"+f"(d[10]),"+f"(d[11]),"+f"(d[12]),"+f"(d[13]),"+f"(d[14]),"+f"(d[15]),"+f"(d[16]),"+f"(d[17]),"+f"(d[18]),"+f"(d[19]),"+f"(d[20]),"+f"(d[21]),"+f"(d[22]),"+f"(d[23]),"+f"(d[24]),"+f"(d[25]),"+f"(d[26]),"+f"(d[27]),"+f"(d[28]),"+f"(d[29]),"+f"(d[30]),"+f"(d[31]),"+f"(d[32]),"+f"(d[33]),"+f"(d[34]),"+f"(d[35]),"+f"(d[36]),"+f"(d[37]),"+f"(d[38]),"+f"(d[39]),"+f"(d[40]),"+f"(d[41]),"+f"(d[42]),"+f"(d[43]),"+f"(d[44]),"+f"(d[45]),"+f"(d[46]),"+f"(d[47]),"+f"(d[48]),"+f"(d[49]),"+f"(d[50]),"+f"(d[51]),"+f"(d[52]),"+f"(d[53]),"+f"(d[54]),"+f"(d[55])
    : "l"(da),"l"(db),"r"(sd));
}
__device__ __forceinline__ void wgmma_ss_n56(float* d, uint64_t da, uint64_t db, int sd) {
  asm volatile("{\n.reg .pred p;\nsetp.ne.b32 p, %30, 0;\nwgmma.mma_async.sync.aligned.m64n56k16.f32.bf16.bf16 {%0,%1,%2,%3,%4,%5,%6,%7,%8,%9,%10,%11,%12,%13,%14,%15,%16,%17,%18,%19,%20,%21,%22,%23,%24,%25,%26,%27}, %28, %29, p, 1, 1, 0, 1;\n}\n"
    : "+f"(d[0]),"+f"(d[1]),"+f"(d[2]),"+f"(d[3]),"+f"(d[4]),"+f"(d[5]),"+f"(d[6]),"+f"(d[7]),"+f"(d[8]),"+f"(d[9]),"+f"(d[10]),"+f"(d[11]),"+f"(d[12]),"+f"(d[13]),"+f"(d[14]),"+f"(d[15]),"+f"(d[16]),"+f"(d[17]),"+f"(d[18]),"+f"(d[19]),"+f"(d[20]),"+f"(d[21]),"+f"(d[22]),"+f"(d[23]),"+f"(d[24]),"+f"(d[25]),"+f"(d[26]),"+f"(d[27])
    : "l"(da),"l"(db),"r"(sd));
}
__device__ __forceinline__ void wgmma_ssk_n80(float* d, uint64_t da, uint64_t db, int sd) {
  asm volatile("{\n.reg .pred p;\nsetp.ne.b32 p, %42, 0;\nwgmma.mma_async.sync.aligned.m64n80k16.f32.bf16.bf16 {%0,%1,%2,%3,%4,%5,%6,%7,%8,%9,%10,%11,%12,%13,%14,%15,%16,%17,%18,%19,%20,%21,%22,%23,%24,%25,%26,%27,%28,%29,%30,%31,%32,%33,%34,%35,%36,%37,%38,%39}, %40, %41, p, 1, 1, 0, 0;\n}\n"
    : "+f"(d[0]),"+f"(d[1]),"+f"(d[2]),"+f"(d[3]),"+f"(d[4]),"+f"(d[5]),"+f"(d[6]),"+f"(d[7]),"+f"(d[8]),"+f"(d[9]),"+f"(d[10]),"+f"(d[11]),"+f"(d[12]),"+f"(d[13]),"+f"(d[14]),"+f"(d[15]),"+f"(d[16]),"+f"(d[17]),"+f"(d[18]),"+f"(d[19]),"+f"(d[20]),"+f"(d[21]),"+f"(d[22]),"+f"(d[23]),"+f"(d[24]),"+f"(d[25]),"+f"(d[26]),"+f"(d[27]),"+f"(d[28]),"+f"(d[29]),"+f"(d[30]),"+f"(d[31]),"+f"(d[32]),"+f"(d[33]),"+f"(d[34]),"+f"(d[35]),"+f"(d[36]),"+f"(d[37]),"+f"(d[38]),"+f"(d[39])
    : "l"(da),"l"(db),"r"(sd));
}
__device__ __forceinline__ void wgmma_rs_n32(float* d, const uint32_t* a, uint64_t db, int sd) {
  asm volatile("{\n.reg .pred p;\nsetp.ne.b32 p, %21, 0;\nwgmma.mma_async.sync.aligned.m64n32k16.f32.bf16.bf16 {%0,%1,%2,%3,%4,%5,%6,%7,%8,%9,%10,%11,%12,%13,%14,%15}, {%16,%17,%18,%19}, %20, p, 1, 1, 1;\n}\n"
    : "+f"(d[0]),"+f"(d[1]),"+f"(d[2]),"+f"(d[3]),"+f"(d[4]),"+f"(d[5]),"+f"(d[6]),"+f"(d[7]),"+f"(d[8]),"+f"(d[9]),"+f"(d[10]),"+f"(d[11]),"+f"(d[12]),"+f"(d[13]),"+f"(d[14]),"+f"(d[15])
    : "r"(a[0]),"r"(a[1]),"r"(a[2]),"r"(a[3]),"l"(db),"r"(sd));
}

constexpr float LOG2E = 1.4426950408889634f;

__device__ __forceinline__ float swiglu(float g, float u, float hr) {
  const float z = g * hr, w = (u * hr) * z;
  return fmaf(w, tanh_approx(z), w);
}
__device__ __forceinline__ uint32_t gate2(float a0, float a1, uint32_t pv) {
  const float z0 = a0 + bf_lo(pv), z1 = a1 + bf_hi(pv);
  return pack2(fmaf(z0, tanh_approx(z0), z0), fmaf(z1, tanh_approx(z1), z1));
}

__device__ __forceinline__ void mma16(float* c, const uint32_t* a, uint32_t b0, uint32_t b1) {
  asm volatile("mma.sync.aligned.m16n8k16.row.col.f32.bf16.bf16.f32 {%0,%1,%2,%3}, {%4,%5,%6,%7}, {%8,%9}, {%0,%1,%2,%3};"
      : "+f"(c[0]), "+f"(c[1]), "+f"(c[2]), "+f"(c[3]) : "r"(a[0]), "r"(a[1]), "r"(a[2]), "r"(a[3]), "r"(b0), "r"(b1));
}
__device__ __forceinline__ void mma8(float* c, const uint32_t* a, uint32_t b) {
  asm volatile("mma.sync.aligned.m16n8k8.row.col.f32.bf16.bf16.f32 {%0,%1,%2,%3}, {%4,%5}, {%6}, {%0,%1,%2,%3};"
      : "+f"(c[0]), "+f"(c[1]), "+f"(c[2]), "+f"(c[3]) : "r"(a[0]), "r"(a[1]), "r"(b));
}
__device__ __forceinline__ void bar7(uint32_t dep) {
  asm volatile("{.reg .pred p; setp.eq.u32 p, %0, 0; bar.red.or.pred p, 7, 256, p;}" ::"r"(dep) : "memory");
}
__device__ __forceinline__ float stdev(float mean, float sq) {
  return rbf(sqrt_approx(rbf(rbf(fmaxf(fmaf(-mean, mean, sq * (1.f / D_)), 0.f)) + 1e-5f)));
}

struct Ring {
  uint32_t st, ph;
  __device__ __forceinline__ void next() { if (++st == NST) { st = 0; ph ^= 1; } }
};

__global__ void __cluster_dims__(2, 1, 1) __launch_bounds__(512, 1) fused_kernel(Scratch* __restrict__ gs, uint4* __restrict__ out, const uint4* __restrict__ x_in, const uint4* __restrict__ wqkv_in, const __grid_constant__ Params p) {
  extern __shared__ __align__(1024) uint8_t smem[];
  const uint32_t sb = s2u(smem);
  const uint32_t bars = sb + OFF_BAR;
  const int tid = threadIdx.x, warp = __shfl_sync(~0u, tid >> 5, 0), lane = tid & 31;
  const int rank = blockIdx.x & 1, cid = blockIdx.x >> 1;
  if (tid == 0) { TG(0); TS(1); }
  if (warp < 12) asm volatile("barrier.cluster.arrive.relaxed.aligned;" ::: "memory");
#define BAR(i) (bars + 8 * (i))
  const uint4* xp = x_in + ((blockIdx.x & 120) + blockIdx.x) * 448;
  if (tid == 256) {
    l2_prefetch(xp, 7168);
    delay(PD1);
    l2_prefetch(xp + 3584, 7168);
    delay(PD2);
    if (blockIdx.x < 112) {
#pragma unroll 1
      for (int i = 0; i < 4; i++) l2_prefetch(wqkv_in + (blockIdx.x + 112 * i) * 168 + 56, 1792);
    }
  }
  int grp, j;
  if (cid < 4) { grp = 0; j = 4 + cid; }
  else if (cid < 36) { grp = (cid - 4) & 7; j = (cid - 4) >> 3; }
  else { j = ((cid - 36) * 37) >> 8; grp = 1 + (cid - 36) - 7 * j; j += 4; }
  const int tb = 2 * grp + rank;
  const int T2 = 2 * grp + (j >> 2);
  const int qn = j & 3;
  const int wg = warp >> 2;
  if (warp < 12) {
  if (warp < 8) {
    const uint32_t xs = sb + (wg == 0 ? OFF_K : 7 * STAGE);
    {
      const int w = warp & 3;
      const uint32_t b0 = BAR(B_X + wg * 7 + w);
      if (lane == 0) {
        mbar_init(b0, 1);
        if (w < 3) mbar_init(b0 + 32, 1);
        fence_async_smem();
        mbar_expect(b0, 8192);
        if (w < 3) mbar_expect(b0 + 32, 8192);
      }
      if (wg == 1) asm volatile("bar.sync 4, 256;" ::: "memory");
      if (lane == 0) {
        tma2d(xs + w * 8192, &p.xm, b0, w * 64, tb * 128 + wg * 64);
        if (w < 3) tma2d(xs + (w + 4) * 8192 + (warp == 6 ? 57344 : 0), &p.xm, b0 + 32, (w + 4) * 64, tb * 128 + wg * 64);
      }
      TSW(2 + wg);
      if (wg == 0) asm volatile("bar.sync 4, 256;" ::: "memory");
    }
    asm volatile("barrier.cluster.wait.acquire.aligned;" ::: "memory");
    asm volatile("setmaxnreg.inc.sync.aligned.u32 208;");
    const int g = lane >> 2, q = lane & 3;
    uint32_t a[112];
    uint32_t m0, m1;
    float mu0, mu1, k0, k1;
    {
      const uint32_t xa = xs + ((warp & 3) * 16 + (lane & 15)) * 128;
      float sq[4][4], sum[2][4];
      zero<16>(&sq[0][0]); zero<8>(&sum[0][0]);
#pragma unroll
      for (int kt = 0; kt < 8; kt++) {
        if (kt < 7) {
          mbar_wait(BAR(B_X + wg * 7 + kt), 0);
          if (kt == 0) TSW(6 + wg);
          if (kt == 6) TSW(8 + wg);
          const uint32_t xk = xa + kt * 8192 + ((kt == 6 && wg == 1) ? 57344 : 0);
#pragma unroll
          for (int ks = 0; ks < 4; ks++) ldsm4(&a[16 * kt + 4 * ks], xk + (((2 * ks + (lane >> 4)) ^ (lane & 7)) << 4));
        }
        if (kt > 0) {
#pragma unroll
          for (int ks = 0; ks < 4; ks++) {
            const uint32_t* f = &a[16 * kt - 16 + 4 * ks];
            mma16(sum[ks & 1], f, 0x3f803f80u, 0x3f803f80u);
            mma8(sq[0], f, f[0]); mma8(sq[1], f, f[1]); mma8(sq[2], f + 2, f[2]); mma8(sq[3], f + 2, f[3]);
          }
        }
      }
      if (lane < 2) mbar_arrive_cluster(mapa(BAR(B_XFREE + wg), lane));
      k0 = (g & 1) ? sq[0][1] + sq[2][1] : sq[0][0] + sq[2][0];
      k1 = (g & 1) ? sq[1][3] + sq[3][3] : sq[1][2] + sq[3][2];
      if (wg == 1) bar7(__float_as_uint(k0) ^ __float_as_uint(k1));
      mu0 = (sum[0][0] + sum[1][0]) * (1.f / D_); mu1 = (sum[0][2] + sum[1][2]) * (1.f / D_);
      m0 = pack2(mu0, mu0); m1 = pack2(mu1, mu1);
#pragma unroll
      for (int i = 0; i < 16; i++) a[i] = sub2(a[i], (i & 1) ? m1 : m0);
      k0 = __shfl_sync(~0u, k0, (lane & 28) + (g >> 1)); k1 = __shfl_sync(~0u, k1, (lane & 28) + (g >> 1));
      TSW(4 + wg);
    }
    const bool rel = (lane == 0) && ((warp & 3) < 2);
    uint32_t rel_base = mapa(bars, rank ^ (warp & 1)) + 8 * B_EMPTY;
    const uint64_t dB128 = mkdesc(sb, 8192, 1024, 1);
    const uint64_t dW = dB128 + (j & 1);
    float rs0, rs1;

    {
      float accK[28], accV[28];
      if (wg == 0) {
        uint32_t d = __float_as_uint(k0);
#pragma unroll
        for (int i = 0; i < 16; i++) d |= a[i];
        bar7(d);
      } else {
        asm volatile("bar.sync 1, 256;" ::: "memory");
      }
#pragma unroll
      for (int kt = 0; kt < 7; kt++) {
        SW(BAR(B_FULL + kt), 0);
        TSW(70 + 2 * kt + wg);
        wg_fence();
#pragma unroll
        for (int ks = 0; ks < 4; ks++) {
          wgmma_rs_n56(accK, &a[(kt * 4 + ks) * 4], dW + (kt * 1024 + ks * 128), kt | ks);
          wgmma_rs_n56(accV, &a[(kt * 4 + ks) * 4], dW + (kt * 1024 + 512 + ks * 128), kt | ks);
        }
        wg_commit();
        if (kt == LAG0 && wg == 0) asm volatile("bar.arrive 1, 256;" ::: "memory");
        if (kt == LAGB && wg == 1) asm volatile("bar.arrive 5, 256;" ::: "memory");
        if (kt < 6) {
#pragma unroll
          for (int i = (kt + 1) * 16; i < (kt + 2) * 16; i++) asm volatile("sub.rn.bf16x2 %0, %0, %1;" : "+r"(a[i]) : "r"((i & 1) ? m1 : m0));
        }
        if (kt > 0) { wg_wait<1>(); if (rel) mbar_arrive_cluster(rel_base + 8 * (kt - 1)); }
      }
      rs0 = rcp(stdev(mu0, k0)); rs1 = rcp(stdev(mu1, k1));
      asm volatile("" : "+f"(rs0), "+f"(rs1));
      wg_wait<0>();
      reg_fence<28>(accK); reg_fence<28>(accV);
      if (rel) mbar_arrive_cluster(rel_base + 8 * 6);
      mbar_wait(BAR(B_XFREE), 0);
      TSW(10 + wg); SDUMP(70 + wg);
      const uint32_t ka = sb + OFF_K + (lane >> 4) * KVB + (2 + 2 * warp + ((lane >> 3) & 1)) * 896 + (lane & 7) * 16;
#pragma unroll
      for (int c = 0; c < 7; c++)
        stsm4(ka + c * 128, pack2(accK[4 * c] * rs0, accK[4 * c + 1] * rs0), pack2(accK[4 * c + 2] * rs1, accK[4 * c + 3] * rs1),
              pack2(accV[4 * c] * rs0, accV[4 * c + 1] * rs0), pack2(accV[4 * c + 2] * rs1, accV[4 * c + 3] * rs1));
      fence_async_smem();
      __syncwarp();
      if (lane == 0) mbar_arrive(BAR(B_KV));
      TSW(12 + wg);
    }
    const float hr0 = 0.5f * rs0, hr1 = 0.5f * rs1;
    const uint32_t tile_off = (lane >> 4) * 1024 + ((warp & 3) * 16 + (lane & 15)) * 16;
    const uint32_t hs_st = sb + OFF_HS + wg * 8192 + tile_off;
    const int bar_mine = 5 - 4 * wg, bar_other = 1 + 4 * wg;

    {
      const uint64_t dB64 = mkdesc(sb + 8192, 4096, 512, 2);
      float accQ[28], accG[32];
      asm volatile("bar.sync %0, 256;" ::"r"(bar_mine) : "memory");
#pragma unroll
      for (int kt = 0; kt < 7; kt++) {
        const int st = (7 + kt) % 10;
        SW(BAR(B_FULL + st), kt >= 3);
        if (kt == 0) TSW(14 + wg);
        wg_fence();
#pragma unroll
        for (int ks = 0; ks < 4; ks++) {
          wgmma_rs_n56(accQ, &a[(kt * 4 + ks) * 4], dW + (st * 1024 + ks * 128), kt | ks);
          wgmma_rs_n64(accG, &a[(kt * 4 + ks) * 4], dB64 + (st * 1024 + ks * 64), kt | ks);
        }
        wg_commit();
        if (kt == LAGA) asm volatile("bar.arrive %0, 256;" ::"r"(bar_other) : "memory");
        if (kt > 0) { wg_wait<1>(); if (rel) mbar_arrive_cluster(rel_base + 8 * ((6 + kt) % 10)); }
      }
      wg_wait<0>();
      reg_fence<28>(accQ); reg_fence<32>(accG);
      if (rel) mbar_arrive_cluster(rel_base + 8 * 3);
      mbar_wait(BAR(B_STG), 0);
      TSW(16 + wg); SDUMP(72 + wg);
      const uint32_t qa = hs_st - (OFF_HS - OFF_Q);
      uint32_t qp[14];
#pragma unroll
      for (int c = 0; c < 7; c++) { qp[2 * c] = pack2(accQ[4 * c] * rs0, accQ[4 * c + 1] * rs0); qp[2 * c + 1] = pack2(accQ[4 * c + 2] * rs1, accQ[4 * c + 3] * rs1); }
      stsm4(qa, qp[0], qp[1], qp[2], qp[3]);
      stsm4(qa + 2048, qp[4], qp[5], q < 2 ? qp[6] : 0u, q < 2 ? qp[7] : 0u);
      stsm4(qa + 4096, q < 2 ? 0u : qp[6], q < 2 ? 0u : qp[7], qp[8], qp[9]);
      stsm4(qa + 6144, qp[10], qp[11], qp[12], qp[13]);
#pragma unroll
      for (int c = 0; c < 2; c++) {
        uint32_t hp[4];
#pragma unroll
        for (int e = 0; e < 2; e++) {
          const float* gg = &accG[8 * c + 4 * e]; const float* uu = &accG[16 + 8 * c + 4 * e];
          hp[2 * e] = pack2(swiglu(gg[0], uu[0], hr0), swiglu(gg[1], uu[1], hr0));
          hp[2 * e + 1] = pack2(swiglu(gg[2], uu[2], hr1), swiglu(gg[3], uu[3], hr1));
        }
        stsm4(hs_st + c * 2048, hp[0], hp[1], hp[2], hp[3]);
      }
      fence_async_smem();
      __syncwarp();
      if (lane < 2) mbar_arrive(BAR(B_Q + wg + 2 * lane));
      TSW(18 + wg);
    }

    Ring rg{4, 1};
#pragma unroll 1
    for (int c3 = 0; c3 < 3; c3++) {
      float acc[64];
      if (c3 == 2) rel_base = mapa(bars, rank) + 8 * B_EMPTY;
      asm volatile("bar.sync %0, 256;" ::"r"(bar_mine) : "memory");
      uint32_t prev = 0;
#pragma unroll
      for (int kt = 0; kt < 7; kt++) {
        SW(BAR(B_FULL + rg.st), rg.ph);
        if (kt == 0) TSW(20 + 6 * c3 + wg);
        const uint64_t db = dB128 + (uint64_t)(rg.st * (STAGE >> 4));
        wg_fence();
#pragma unroll
        for (int ks = 0; ks < 4; ks++) wgmma_rs_n128(acc, &a[(kt * 4 + ks) * 4], db + ks * 128, kt | ks);
        wg_commit();
        if (kt == LAGP4 || kt == LAGA) { if ((kt == LAGP4) == (c3 == 2 && wg == 0)) asm volatile("bar.arrive %0, 256;" ::"r"(bar_other) : "memory"); }
        if (kt > 0) { wg_wait<1>(); if (rel) mbar_arrive_cluster(rel_base + 8 * prev); }
        prev = rg.st; rg.next();
      }
      wg_wait<0>();
      reg_fence<64>(acc);
      if (rel) mbar_arrive_cluster(rel_base + 8 * prev);
      mbar_wait(BAR(B_HFREE + wg), c3 & 1);
      TSW(22 + 6 * c3 + wg); SDUMP(74 + 2 * c3 + wg);
#pragma unroll
      for (int c = 0; c < 4; c++) {
        uint32_t hp[4];
#pragma unroll
        for (int e = 0; e < 4; e++) { const int i = 8 * c + 2 * e; const float hr = (i & 2) ? hr1 : hr0; hp[e] = pack2(swiglu(acc[i], acc[32 + i], hr), swiglu(acc[i + 1], acc[33 + i], hr)); }
        stsm4(hs_st + c * 2048, hp[0], hp[1], hp[2], hp[3]);
      }
      fence_async_smem();
      __syncwarp();
      if (lane == 0) mbar_arrive(BAR(B_H + wg));
      TSW(24 + 6 * c3 + wg);
    }

    uint64_t dA = mkdesc(sb, 1024, 128, 0);
    const uint64_t dBn = mkdesc(sb, 128, 1024, 0);
    uint64_t dWo = dBn + (OFF_WOB >> 4);
    const bool rel2 = (tid & 127) == 0;
    float dacc[56], sacc[28];
    uint32_t xr[14];
    auto wo_step = [&](int k, int slot) { wgmma_ss_n56(sacc, dA + (((slot + (k >> 3)) % 10) * 1024 + (k & 7) * 128), dWo + ((k >> 2) * 448 + (k & 3) * 16), k); };
    auto load_x = [&](int slot) {
      const uint32_t xra = sb + slot * STAGE + 8192 + ((warp & 3) * 16 + (lane & 15)) * 112 + (lane >> 4) * 16;
#pragma unroll
      for (int c = 0; c < 3; c++) ldsm4(&xr[4 * c], xra + c * 32);
      asm volatile("ldmatrix.sync.aligned.m8n8.x2.shared.b16 {%0,%1}, [%2];" : "=r"(xr[12]), "=r"(xr[13]) : "r"(xra + 96) : "memory");
    };
    mbar_wait(BAR(B_WOB), 0);
    if (wg == 0) {
      mbar_wait(BAR(B_FULL2), 0);
      mbar_wait(BAR(B_FULL2 + 1), 0);
      load_x(8);
      asm volatile("bar.sync 5, 256;" ::: "memory");
      TSW(112);
      wg_fence();
#pragma unroll
      for (int k = 0; k < 16; k++) wo_step(k, 5);
      wg_commit();
      wo_step(16, 5);
      wg_commit();
      wg_wait<1>();
      if (rel2) mbar_arrive(BAR(B_EMPTY2));
      asm volatile("bar.arrive 1, 256;" ::: "memory");
#pragma unroll
      for (int k = 17; k < 28; k++) wo_step(k, 5);
      wg_commit();
    } else {
      asm volatile("bar.sync 1, 256;" ::: "memory");
    }
    int pr = 2, ph = 0, prev = 1;
#pragma unroll 1
    for (int kt = 0; kt < 14; kt++) {
      SW(BAR(B_FULL2 + pr), ph);
      TSW(84 + 2 * kt + wg);
      const uint64_t da = dA + (uint32_t)((pr < 3 ? 5 + 2 * pr : 2 * pr - 5) * 1024 + wg * 512);
      const uint64_t db = dBn + (uint32_t)((pr < 2 ? 6 + 2 * pr : 2 * pr - 4) * 1024);
      if (kt == LEAD && wg == 1) asm volatile("bar.sync 6, 256;" ::: "memory");
      wg_fence();
#pragma unroll
      for (int ks = 0; ks < 4; ks++) wgmma_ss_n112(dacc, da + ks * 128, db + ks * 16, kt | ks);
      wg_commit();
      if (kt == 13 && wg == 0) asm volatile("bar.arrive 6, 256;" ::: "memory");
      wg_wait<1>();
      if (rel2 && kt >= wg) mbar_arrive(BAR(B_EMPTY2 + prev));
      prev = pr;
      if (++pr == 5) { pr = 0; ph ^= 1; }
    }
    asm volatile("" : "+l"(dA), "+l"(dWo));
    const uint32_t part = sb + OFF_PART + warp * 1792;
    uint4* outp = out + (T2 * 128 + warp * 16) * 56 + qn * 14 + rank * 7;
    {
      mbar_wait(BAR(B_PFREE), 0);
      const uint32_t dst = mapa(part, rank ^ 1) + lane * 16, pb = mapa(BAR(B_PART + 2 * wg), rank ^ 1);
      wg_wait<0>();
      reg_fence<56>(dacc);
      TSW(38 + wg); SDUMP(80 + wg);
#pragma unroll
      for (int i = 0; i < 4; i++) {
        const float* d = &dacc[28 + 8 * i];
        if (i < 3)
          asm volatile("st.async.shared::cluster.mbarrier::complete_tx::bytes.v4.b32 [%0], {%1,%2,%3,%4}, [%5];"
                       ::"r"(dst + i * 512), "r"(pack2(d[0], d[1])), "r"(pack2(d[2], d[3])), "r"(pack2(d[4], d[5])), "r"(pack2(d[6], d[7])), "r"(pb + (i >> 1) * 8) : "memory");
        else
          asm volatile("st.async.shared::cluster.mbarrier::complete_tx::bytes.v2.b32 [%0], {%1,%2}, [%3];"
                       ::"r"(dst + 1536 - lane * 8), "r"(pack2(d[0], d[1])), "r"(pack2(d[2], d[3])), "r"(pb + 8) : "memory");
      }
      TSW(40 + wg);
      if (wg == 1) {
        mbar_wait(BAR(B_FULL2 + 1), 1);
        TSW(113);
        wg_fence();
#pragma unroll
        for (int k = 0; k < 16; k++) wo_step(k, 7);
        mbar_wait(BAR(B_FULL2 + 2), 1);
        TSW(115);
        load_x(0);
        wg_fence();
#pragma unroll
        for (int k = 16; k < 28; k++) wo_step(k, 7);
        wg_commit();
        TSW(117);
      }
      uint32_t gp[14];
      mbar_wait(BAR(B_PART + 2 * wg), 0);
      TSW(120 + wg);
      lds128v(&gp[0], part + lane * 16); lds128v(&gp[4], part + 512 + lane * 16);
#pragma unroll
      for (int i = 0; i < 8; i++) gp[i] = gate2(dacc[2 * i], dacc[2 * i + 1], gp[i]);
      TSW(114 + 2 * wg);
      mbar_wait(BAR(B_PART + 2 * wg + 1), 0);
      TSW(118 + wg);
      lds128v(&gp[8], part + 1024 + lane * 16);
      asm volatile("ld.shared.v2.u32 {%0,%1}, [%2];" : "=r"(gp[12]), "=r"(gp[13]) : "r"(part + 1536 + lane * 8) : "memory");
#pragma unroll
      for (int i = 8; i < 14; i++) gp[i] = gate2(dacc[2 * i], dacc[2 * i + 1], gp[i]);
#pragma unroll
      for (int i = 0; i < 14; i++) asm volatile("" : "+r"(gp[i])::"memory");
      TSW(122 + wg);
      if (lane == 0) mbar_arrive(BAR(B_DONE));
      wg_wait<0>();
      reg_fence<28>(sacc);
      TSW(42 + wg);
      uint32_t yo[14];
#pragma unroll
      for (int c = 0; c < 14; c++) yo[c] = add2(xr[c], mul2(pack2(sacc[2 * c], sacc[2 * c + 1]), gp[c]));
      __syncwarp();
      const uint32_t oa = part + (lane & 15) * 112 + (lane >> 4) * 16;
#pragma unroll
      for (int c = 0; c < 3; c++) stsm4(oa + c * 32, yo[4 * c], yo[4 * c + 1], yo[4 * c + 2], yo[4 * c + 3]);
      stsm2(oa + 96, yo[12], yo[13]);
      __syncwarp();
      uint32_t y[16];
#pragma unroll
      for (int i = 0; i < 4; i++) if (i < 3 || lane < 16) lds128v(&y[4 * i], part + lane * 16 + i * 512);
#pragma unroll
      for (int i = 0; i < 4; i++) {
        const int c = lane + 32 * i, r = (c * 147) >> 10;
        if (i < 3 || lane < 16) outp[r * 49 + c] = make_uint4(y[4 * i], y[4 * i + 1], y[4 * i + 2], y[4 * i + 3]);
      }
    }
    TSW(44 + wg);
    FIN;
  } else {
    asm volatile("setmaxnreg.dec.sync.aligned.u32 72;");
    asm volatile("barrier.cluster.wait.acquire.aligned;" ::: "memory");
    const int w = warp & 3, g = lane >> 2, q = lane & 3;
    {
      const bool two = blockIdx.x < 12;
      if (tid == 256) {
        const int u = blockIdx.x;
        prefetch_map(&p.wdm); prefetch_map(&p.wom);
        mbar_wait(BAR(B_XFREE), 0);
        mbar_wait(BAR(B_XFREE + 1), 0);
        TS(124);
        mbar_expect(BAR(B_RT), two ? 28672 : 14336);
        tma2d(sb + OFF_Q, u < 112 ? &p.wdm : &p.wom, BAR(B_RT), (u & 3) * 112, ((u >> 2) - (u < 112 ? 0 : 28)) * 64);
        if (two) tma2d(sb + OFF_Q + 14336, &p.wom, BAR(B_RT), (u & 3) * 112, ((u >> 2) + 4) * 64);
      }
      const int row = tid & 63, c0 = ((tid >> 6) ^ (tid >> 2)) & 1;
      mbar_wait(BAR(B_RT), 0);
      TSW(125);
#pragma unroll 1
      for (uint32_t stg = sb + OFF_Q; stg <= sb + OFF_Q + two * 14336; stg += 14336) {
        uint32_t v[28];
#pragma unroll
        for (int i = 0; i < 7; i++) lds128v(&v[4 * i], stg + row * 224 + c0 * 16 + i * 32);
        asm volatile("bar.sync 2, 128;" ::: "memory");
#pragma unroll
        for (int i = 0; i < 7; i++) sts128(stg + c0 * 1024 + row * 16 + i * 2048, make_uint4(v[4 * i], v[4 * i + 1], v[4 * i + 2], v[4 * i + 3]));
      }
      fence_async_smem();
      asm volatile("bar.sync 2, 128;" ::: "memory");
      TSW(51);
      if (warp == 8) {
        const int u = blockIdx.x + (lane >> 1) * 128, e = lane & 1;
        if (u < 140) {
          uint4* dst = u < 112 ? gs->wd + ((u & 3) * 28 + (u >> 2)) * 896 + (e ^ (u >= 56)) * 448 : gs->wo + (2 * (u & 3) + e) * 3136 + ((u >> 2) - 28) * 448;
          bulk_s2g(dst, sb + OFF_Q + lane * 7168, 7168);
          bulk_commit();
        }
        asm volatile("cp.async.bulk.wait_group.read 0;" ::: "memory");
        __syncwarp();
        if (lane == 0) { mbar_arrive(BAR(B_STG)); TS(68); }
        bulk_wait0();
        __syncwarp();
        if (lane == 0) { flag_add(&gs->flag[F_W * 8]); TS(67); }
      }
    }
    const int par = g & 1;
    const float sl2 = 0.1889822365046136f * LOG2E;
    uint32_t o3a = 0, o3b = 0;
    mbar_wait(BAR(B_KV), 0);
    mbar_wait(BAR(B_HALO), 0);
    if (rank == 1 && tid == 256) mbar_arrive_cluster(mapa(BAR(B_KVFREE), 0));
#pragma unroll 1
    for (int it = 0; it < 4; it++) {
      const int mt = it >> 1, hh = it & 1;
      mbar_wait(BAR(B_Q + mt), 0);
      if (it == 3 && tid == 256) { bulk_wait0(); flag_add(&gs->flag[(F_O + 2 * tb) * 8]); }
      if (hh == 0) TSW(46 + 2 * mt);
      const uint64_t dQ = mkdesc(sb + OFF_Q, 1024, 128, 0) + (uint64_t)(mt * 512 + hh * 256);
      const uint64_t dK = mkdesc(sb + OFF_K, 128, 896, 0) + (uint64_t)(mt * 448 + hh * 24);
      const uint64_t dV = mkdesc(sb + OFF_V, 896, 128, 0) + (uint64_t)(mt * 448 + hh * 24);
      const int jmin = 16 - (tb * 128 + mt * 64 + w * 16);
      float s[40];
      wg_fence();
      wgmma_ssk_n80(s, dQ, dK, 0);
      wgmma_ssk_n80(s, dQ + 128, dK + 16, 1);
      wg_commit();
      wg_wait<0>();
      reg_fence<40>(s);
      float u[20], v[12], l[8];
#pragma unroll
      for (int i = 0; i < 20; i++) u[i] = par ? s[2 * i + 1] : s[2 * i];
#pragma unroll
      for (int i = 0; i < 12; i++) v[i] = (w & 2) ? u[i + 8] : u[i];
      float m0 = -INFINITY, m1 = -INFINITY;
#pragma unroll
      for (int n = 0; n < 4; n++) {
        const int jj = 8 * n + 2 * q + par;
        const uint32_t d0 = g + 16 - jj, d1 = d0 + 8;
        l[2 * n] = (n < 3 && jj >= jmin && d0 <= 14) ? ((w & 1) ? v[2 * n + 4] : v[2 * n]) : -INFINITY;
        l[2 * n + 1] = (n > 0 && jj >= jmin && d1 <= 14) ? ((w & 1) ? v[2 * n + 5] : v[2 * n + 1]) : -INFINITY;
        m0 = fmaxf(m0, l[2 * n]); m1 = fmaxf(m1, l[2 * n + 1]);
      }
      m0 = fmaxf(m0, __shfl_xor_sync(~0u, m0, 1)); m1 = fmaxf(m1, __shfl_xor_sync(~0u, m1, 1));
      m0 = fmaxf(m0, __shfl_xor_sync(~0u, m0, 2)); m1 = fmaxf(m1, __shfl_xor_sync(~0u, m1, 2));
      float z0 = 0.f, z1 = 0.f;
#pragma unroll
      for (int n = 0; n < 4; n++) {
        l[2 * n] = n < 3 ? ex2((l[2 * n] - m0) * sl2) : 0.f; l[2 * n + 1] = n > 0 ? ex2((l[2 * n + 1] - m1) * sl2) : 0.f;
        z0 += l[2 * n]; z1 += l[2 * n + 1];
      }
      z0 += __shfl_xor_sync(~0u, z0, 1); z1 += __shfl_xor_sync(~0u, z1, 1);
      z0 += __shfl_xor_sync(~0u, z0, 2); z1 += __shfl_xor_sync(~0u, z1, 2);
      const float i0 = rcp(z0), i1 = rcp(z1);
      uint32_t pf[8];
#pragma unroll
      for (int i = 0; i < 8; i++) pf[i] = (i == 1 || i == 6) ? 0u : pack2(l[i] * ((i & 1) ? i1 : i0), 0.f) << (16 * par);
      uint32_t pa[5][4];
#pragma unroll
      for (int k = 0; k < 5; k++)
#pragma unroll
        for (int r = 0; r < 4; r++) pa[k][r] = (k < 4 && k == w) ? pf[r] : ((k > 0 && k == w + 1) ? pf[4 + r] : 0u);
      float o[16];
      wg_fence();
#pragma unroll
      for (int k = 0; k < 5; k++) wgmma_rs_n32(o, pa[k], dV + k * 112, k);
      wg_commit();
      wg_wait<0>();
      reg_fence<16>(o);
      const uint32_t qa = sb + OFF_Q + mt * 8192 + hh * 3072 + (lane >> 4) * 1024 + (w * 16 + (lane & 15)) * 16;
      const bool keep = hh && q < 2;
      stsm4(qa, keep ? o3a : pack2(o[0], o[1]), keep ? o3b : pack2(o[2], o[3]), pack2(o[4], o[5]), pack2(o[6], o[7]));
      o3a = pack2(o[12], o[13]); o3b = pack2(o[14], o[15]);
      stsm4(qa + 2048, pack2(o[8], o[9]), pack2(o[10], o[11]), o3a, o3b);
      if (hh) {
        fence_async_smem();
        asm volatile("bar.sync 2, 128;" ::: "memory");
        if (tid == 256) {
          bulk_s2g(gs->o + ((tb * 2 + mt) * 56 + 7 * j) * 64, sb + OFF_Q + mt * 8192, 7168);
          bulk_commit();
        }
        TSW(47 + 2 * mt);
      }
    }
    if (lane != 0) return;
    if (tid == 256) {
      bulk_wait0();
      TS(50);
      flag_add(&gs->flag[(F_O + 2 * tb + 1) * 8]);
      mbar_wait(BAR(B_WOK), 0);
      mbar_wait(BAR(B_KVFREE), 0);
      mbar_expect(BAR(B_WOB), 50176);
      bulk_g2s(sb + OFF_WOB, gs->wo + (2 * qn + rank) * 3136, 50176, BAR(B_WOB));
      mbar_arrive(BAR(B_DONE));
    }
  }
  } else {
    asm volatile("setmaxnreg.dec.sync.aligned.u32 24;");
    if (lane == 0) {
      if (warp == 12) {
        prefetch_map(&p.wqkv);
#pragma unroll
        for (int i = 0; i < B_PART; i++) mbar_init(BAR(i), 1);
        mbar_init(BAR(B_KV), 8); mbar_init(BAR(B_XFREE), 8); mbar_init(BAR(B_XFREE + 1), 8); mbar_init(BAR(B_DONE), 10 + 2 * PSTEP); mbar_init(BAR(B_RT), 1);
      } else if (warp == 13) {
#pragma unroll
        for (int i = B_PART; i < B_X; i++) mbar_init(BAR(i), 1);
#pragma unroll
        for (int i = 0; i < 4; i++) mbar_expect(BAR(B_PART + i), 4096 - (i & 1) * 1024);
        if (rank) mbar_expect(BAR(B_HALO), 3584);
      } else if (warp == 14) {
#pragma unroll
        for (int i = B_ORDY; i < B_EMPTY; i++) mbar_init(BAR(i), i < B_FULL2 ? 1 : 2);
        mbar_arrive(BAR(B_EMPTY2)); mbar_arrive(BAR(B_EMPTY2 + 1));
      } else {
#pragma unroll
        for (int i = B_EMPTY; i < B_KV; i++) mbar_init(BAR(i), 4);
      }
      asm volatile("fence.mbarrier_init.release.cluster;" ::: "memory");
    }
    __syncwarp();
    asm volatile("barrier.cluster.arrive.relaxed.aligned;" ::: "memory");
    asm volatile("barrier.cluster.wait.acquire.aligned;" ::: "memory");
    if (warp == 13) {
      const uint32_t epoch = *(volatile uint32_t*)&gs->flag[(F_EPOCH + blockIdx.x) * 8] + 1;
      if (rank == 0) {
        mbar_wait_lim(BAR(B_KV), 0);
        if (tb == 0) {
#pragma unroll 1
          for (int c = lane; c < 224; c += 32) sts128(sb + (c < 112 ? OFF_K : OFF_V - 1792) + c * 16, make_uint4(0, 0, 0, 0));
          fence_async_smem();
          __syncwarp();
          if (lane == 0) mbar_arrive(BAR(B_HALO));
        } else {
          const uint32_t* f = &gs->flag[(F_HALO + (tb - 1) * 8 + j) * 8];
          int it = 0;
          while ((int32_t)(ld_flag(f) - epoch) < 0) { if (++it > (1 << 20)) __trap(); }
          fence_async_global();
          if (lane == 0) mbar_expect(BAR(B_HALO), 3584);
          __syncwarp();
          if (lane < 2) bulk_g2s(sb + OFF_K + lane * KVB, gs->halo + ((tb - 1) * 8 + j) * 224 + lane * 112, 1792, BAR(B_HALO));
          if (lane == 0) TS(55);
        }
      }
      const int box = lane < 2 ? 12 + lane : lane - 2;
      const uint32_t* flag = &gs->flag[(lane < 14 ? F_H + (T2 * 2 + rank) * 14 + box : (lane < 16 ? F_O + 2 * T2 - 14 + lane : F_W)) * 8];
      const uint32_t target = epoch * (lane < 2 ? 4 : (lane < 14 ? 2 : (lane < 16 ? 8 : 128)));
      mbar_wait_lim(BAR(B_GO), 0);
      bool pend = lane < 17;
      int it = 0;
      while (true) {
        if (pend && (int32_t)(ld_flag(flag) - target) >= 0) {
          fence_async_global();
          mbar_arrive(BAR(B_X + lane));
          pend = false;
          if (lane == 10) TS(57);
          if (lane == 13) TS(58);
        }
        if (!__any_sync(~0u, pend)) break;
        if (++it > (1 << 20)) __trap();
      }
      if (lane == 0) gs->flag[(F_EPOCH + blockIdx.x) * 8] = epoch;
      mbar_wait_lim(BAR(B_DONE), 0);
      FIN;
    } else if (lane == 0) {
      if (warp == 14) {
        mbar_wait(BAR(B_KV), 0);
        if (rank == 0) {
          const uint32_t hb = mapa(BAR(B_HALO), 1);
          bulk_s2s(mapa(sb + OFF_K, 1), sb + OFF_K + 16 * 896, 1792, hb);
          bulk_s2s(mapa(sb + OFF_V, 1), sb + OFF_V + 16 * 896, 1792, hb);
        } else {
          uint4* dst = gs->halo + (tb * 8 + j) * 224;
          bulk_s2g(dst, sb + OFF_K + 16 * 896, 1792);
          bulk_s2g(dst + 112, sb + OFF_V + 16 * 896, 1792);
          bulk_commit();
          bulk_wait0();
          flag_add(&gs->flag[(F_HALO + tb * 8 + j) * 8]);
          TS(60);
          mbar_arrive(BAR(B_KVFREE));
        }
        const int hb = (tb * 2 + (j >> 2)) * 14;
#pragma unroll 1
        for (int i = 0; i < 8; i++) {
          const int ps = i >> 1, w = i & 1;
          const int box = hb + (ps == 0 ? 12 + (qn >> 1) : 4 * (ps - 1) + qn);
          mbar_wait(BAR(B_H + w), ps & 1);
          bulk_s2g(gs->h + box * 1024 + w * 512 + (ps == 0 ? (qn & 1) * 256 : 0), sb + OFF_HS + w * 8192, ps == 0 ? 4096 : 8192);
          bulk_commit();
          bulk_wait0();
          flag_add(&gs->flag[(F_H + box) * 8]);
          mbar_arrive(BAR(B_HFREE + w));
          if (ps >= 2) TS(63 + 2 * (ps - 2) + w);
        }
        mbar_arrive_cluster(mapa(BAR(B_PFREE), rank ^ 1));
        mbar_arrive(BAR(B_DONE));
        FIN;
      } else {
        if (warp == 12)
        {
          if (warp == 12) TS(52);
          prefetch_map(&p.wg32); prefetch_map(&p.wu32); prefetch_map(rank ? &p.wu : &p.wg); prefetch_map(&p.xr);
          Ring rg{0, 1};
          const int fbase = (j >> 2) * 896;
          const int cq = j * 56 - (j & 1) * 8;
          int i = 0;
#pragma unroll 1
          for (int ps = 0; ps < 5; ps++) {
            const bool two = ps == 1 && rank == 1;
            const CUtensorMap* m = two ? &p.wg32 : (ps < 2 ? &p.wqkv : (rank ? &p.wu : &p.wg));
            const int c0 = two ? fbase + 768 + qn * 32 : (ps == 0 ? cq + D_ + D_ * rank : (ps == 1 ? cq : fbase + (4 * (ps - 2) + qn) * 64));
            if (ps == 1) mbar_wait(BAR(B_XFREE + 1), 0);
#pragma unroll 1
            for (int kt = 0; kt < 7; kt++, i++) {
              mbar_wait(BAR(B_EMPTY + rg.st), rg.ph);
              const uint32_t fb = BAR(B_FULL + rg.st), dst = sb + rg.st * STAGE + rank * 8192;
              mbar_expect(fb, STAGE);
              tma2d_mc(dst, m, fb, c0, kt * 64);
              if (two) tma2d_mc(dst + 4096, &p.wu32, fb, c0, kt * 64);
              rg.next();
              if (i == 35 - NST) mbar_arrive(BAR(B_GO));
            }
          }
          if (warp == 12) TS(53);
        }
      }
    } else {
      return;
    }
  }
  __syncwarp();
  if (((PMASK >> warp) & 1) && lane == 0) {
    const int isB = ~warp & 1;
    mbar_wait(BAR(B_WOK), 0);
    const int tile = isB ? 896 : 1024;
    const uint32_t src = isB ? (offsetof(Scratch, wd) >> 4) + (qn * 28 + rank * 14) * 896 : (T2 * 2 + rank) * 14 * 1024;
    const uint32_t osrc = (offsetof(Scratch, o) >> 4) + T2 * 2 * 56 * 64 + isB * 1024;
    int pr = PFIRST;
#pragma unroll 1
    for (int s = pr; s < 18; s += PSTEP) {
      int sl = 5 + isB + 2 * pr;
      if (sl >= 10) sl -= 10;
      const bool isO = !(s & 14);
      const bool last = isO && (s & isB);
      const uint4* from = gs->h + (isO ? osrc + (s >> 4) * 3584 + (s & 1) * 2048 : src + (s < 4 ? 10 + s : s - 4) * tile);
      if (isO || !isB) mbar_wait(BAR(isO ? B_ORDY + (s >> 4) : B_X - 2 + s), !isO);
      mbar_wait(BAR(B_EMPTY + 5), 0);
      mbar_wait(BAR(s < 5 ? B_EMPTY + sl : B_EMPTY2 + pr), s < 5 ? sl < 5 : (s >= 10 && s < 15));
      const int bytes = isO ? (last ? 8192 : STAGE) : tile * 16;
      mbar_expect(BAR(B_FULL2 + pr), last ? 8192 + 7168 : bytes);
      bulk_g2s(sb + sl * STAGE, from, bytes, BAR(B_FULL2 + pr));
      if (last) tma2d(sb + sl * STAGE + 8192, &p.xr, BAR(B_FULL2 + pr), qn * 112 + rank * 56, T2 * 128 + (s >> 4) * 64);
      if (!isB) { if (s == 0) TS(56); if (s == 12) TS(61); if (s == 15) TS(62); if (s == 17) TS(59); }
      pr += PSTEP;
      if (pr >= 5) pr -= 5;
    }
    mbar_arrive(BAR(B_DONE));
  }
#undef BAR
}

typedef CUresult (*EncFn)(CUtensorMap*, CUtensorMapDataType, cuuint32_t, void*, const cuuint64_t*, const cuuint64_t*,
                          const cuuint32_t*, const cuuint32_t*, CUtensorMapInterleave, CUtensorMapSwizzle,
                          CUtensorMapL2promotion, CUtensorMapFloatOOBfill);

void enc2d(EncFn enc, CUtensorMap* m, const void* ptr, int cols, int rows, int bc, int br, CUtensorMapSwizzle sw) {
  cuuint64_t gd[2] = {(cuuint64_t)cols, (cuuint64_t)rows};
  cuuint64_t gs[1] = {(cuuint64_t)cols * 2};
  cuuint32_t bd[2] = {(cuuint32_t)bc, (cuuint32_t)br}, es[2] = {1, 1};
  enc(m, CU_TENSOR_MAP_DATA_TYPE_BFLOAT16, 2, const_cast<void*>(ptr), gd, gs, bd, es, CU_TENSOR_MAP_INTERLEAVE_NONE, sw,
      CU_TENSOR_MAP_L2_PROMOTION_L2_128B, CU_TENSOR_MAP_FLOAT_OOB_FILL_NONE);
}

}

extern "C" void kernel_launch(void* const* d_in, const int* in_sizes, int n_in, void* d_out, int out_size) {
  static EncFn enc = nullptr;
  static Scratch* gs = nullptr;
  if (!enc) {
    cudaGetSymbolAddress((void**)&gs, g_s);
    void* fn = nullptr;
    cudaDriverEntryPointQueryResult qr;
    cudaGetDriverEntryPoint("cuTensorMapEncodeTiled", &fn, cudaEnableDefault, &qr);
    enc = (EncFn)fn;
    cudaFuncSetAttribute(fused_kernel, cudaFuncAttributeMaxDynamicSharedMemorySize, SMEM_BYTES);
  }
  Params p;
  enc2d(enc, &p.xm, d_in[0], D_, S_, 64, 64, CU_TENSOR_MAP_SWIZZLE_128B);
  enc2d(enc, &p.wqkv, d_in[1], 3 * D_, D_, 64, 64, CU_TENSOR_MAP_SWIZZLE_128B);
  enc2d(enc, &p.wg, d_in[4], F_, D_, 64, 64, CU_TENSOR_MAP_SWIZZLE_128B);
  enc2d(enc, &p.wu, d_in[5], F_, D_, 64, 64, CU_TENSOR_MAP_SWIZZLE_128B);
  enc2d(enc, &p.wg32, d_in[4], F_, D_, 32, 64, CU_TENSOR_MAP_SWIZZLE_64B);
  enc2d(enc, &p.wu32, d_in[5], F_, D_, 32, 64, CU_TENSOR_MAP_SWIZZLE_64B);
  enc2d(enc, &p.wdm, d_in[6], D_, F_, 112, 64, CU_TENSOR_MAP_SWIZZLE_NONE);
  enc2d(enc, &p.wom, d_in[2], D_, D_, 112, 64, CU_TENSOR_MAP_SWIZZLE_NONE);
  enc2d(enc, &p.xr, d_in[0], D_, S_, 56, 64, CU_TENSOR_MAP_SWIZZLE_NONE);
  fused_kernel<<<128, 512, SMEM_BYTES>>>(gs, (uint4*)d_out, (const uint4*)d_in[0], (const uint4*)d_in[1], p);
}
```

```cpp
#include <cuda_runtime.h>
#include <cuda_bf16.h>
#include <cuda.h>
#include <stdint.h>
#include <stddef.h>

namespace {

constexpr int S_ = 2048, D_ = 448, F_ = 1792;
constexpr int NST = 10;
constexpr int STAGE = 16384;
constexpr int KVB = 18 * 896;
constexpr int OFF_K = NST * STAGE;
constexpr int OFF_V = OFF_K + KVB;
constexpr int OFF_Q = OFF_V + KVB;
constexpr int OFF_HS = OFF_K + 50176;
constexpr int OFF_WOB = OFF_K;
constexpr int OFF_PART = OFF_HS;
constexpr int OFF_BAR = OFF_HS + 16384;
constexpr int SMEM_BYTES = OFF_BAR + 1024;
constexpr int B_FULL = 0, B_HFREE = 10  , B_PART = 12  , B_HALO = 16, B_GO = 17, B_PFREE = 18,
              B_X = 19  , B_ORDY = 33  , B_WOK = 35, B_KVFREE = 36, B_WOB = 37, B_STG = 38,
              B_FULL2 = 39  , B_EMPTY2 = 44  ,
              B_EMPTY = 49, B_Q = 59  , B_H = 61  ,
              B_KV = 63, B_XFREE = 64  , B_DONE = 66, B_RT = 67;
#define LEAD 12
#define LAG0 6
#define LAGP4 5
#define PD1 400
#define PD2 200
#define PSTEP 1
#define PMASK 0x9000
#define PFIRST 0
#define LAGA 6
#define LAGB 6

struct Params {
  CUtensorMap xm, wqkv, wg, wu, wg32, wu32, wdm, wom, xr;
};

struct Scratch {
  uint4 h[S_ * F_ / 8];
  uint4 o[S_ * D_ / 8];
  uint4 wd[F_ * D_ / 8];
  uint4 wo[D_ * D_ / 8];
  uint4 halo[16 * 8 * 224];
  uint32_t flag[(448 + 32 + 1 + 128 + 128) * 8];
};
constexpr int F_H = 0, F_O = 448, F_W = 480, F_HALO = 481, F_EPOCH = 609;
__device__ Scratch g_s;
#define TS(slot)
#define TG(slot)
#define TSW(slot)
#define FIN return

#define SW(b, ph) mbar_wait(b, ph)
#define SDUMP(slot)
__device__ __forceinline__ uint32_t s2u(const void* p) { return (uint32_t)__cvta_generic_to_shared(p); }
__device__ __forceinline__ void mbar_init(uint32_t b, int c) { asm volatile("mbarrier.init.shared::cta.b64 [%0], %1;" ::"r"(b), "r"(c) : "memory"); }
__device__ __forceinline__ void mbar_expect(uint32_t b, int bytes) { asm volatile("mbarrier.arrive.expect_tx.shared::cta.b64 _, [%0], %1;" ::"r"(b), "r"(bytes) : "memory"); }
__device__ __forceinline__ void mbar_arrive(uint32_t b) { asm volatile("mbarrier.arrive.shared::cta.b64 _, [%0];" ::"r"(b) : "memory"); }
__device__ __forceinline__ void mbar_arrive_cluster(uint32_t b) { asm volatile("mbarrier.arrive.shared::cluster.b64 _, [%0];" ::"r"(b) : "memory"); }
__device__ __forceinline__ uint32_t mapa(uint32_t a, uint32_t r) { uint32_t o; asm volatile("mapa.shared::cluster.u32 %0, %1, %2;" : "=r"(o) : "r"(a), "r"(r)); return o; }
__device__ __forceinline__ void mbar_wait(uint32_t b, uint32_t ph) {
  asm volatile("{\n.reg .pred p;\nW: mbarrier.try_wait.parity.shared::cta.b64 p, [%0], %1;\n@!p bra W;\n}" ::"r"(b), "r"(ph) : "memory");
}
__device__ __forceinline__ void mbar_wait_lim(uint32_t b, uint32_t ph) {
  uint32_t ok;
  int it = 0;
  do {
    if (++it > (1 << 18)) __trap();
    asm volatile("{.reg .pred p; mbarrier.try_wait.parity.shared::cta.b64 p, [%1], %2; selp.u32 %0,1,0,p;}" : "=r"(ok) : "r"(b), "r"(ph) : "memory");
  } while (!ok);
}
__device__ __forceinline__ uint32_t ld_flag(const uint32_t* f) { uint32_t v; asm volatile("ld.relaxed.gpu.global.u32 %0, [%1];" : "=r"(v) : "l"(f) : "memory"); return v; }
__device__ __forceinline__ void flag_add(uint32_t* f) { asm volatile("red.relaxed.gpu.global.add.u32 [%0], 1;" ::"l"(f) : "memory"); }
__device__ __forceinline__ void fence_async_smem() { asm volatile("fence.proxy.async.shared::cta;" ::: "memory"); }
__device__ __forceinline__ void fence_async_global() { asm volatile("fence.proxy.async.global;" ::: "memory"); }

__device__ __forceinline__ void tma2d(uint32_t dst, const CUtensorMap* m, uint32_t bar, int c0, int c1) {
  asm volatile("cp.async.bulk.tensor.2d.shared::cluster.global.mbarrier::complete_tx::bytes [%0], [%1, {%3,%4}], [%2];" ::"r"(dst), "l"(m), "r"(bar), "r"(c0), "r"(c1) : "memory");
}
__device__ __forceinline__ void tma2d_mc(uint32_t dst, const CUtensorMap* m, uint32_t bar, int c0, int c1) {
  asm volatile("cp.async.bulk.tensor.2d.shared::cluster.global.mbarrier::complete_tx::bytes.multicast::cluster [%0], [%1, {%3,%4}], [%2], %5;" ::"r"(dst), "l"(m), "r"(bar), "r"(c0), "r"(c1), "h"((uint16_t)3) : "memory");
}
__device__ __forceinline__ void bulk_g2s(uint32_t dst, const void* src, int bytes, uint32_t bar) {
  asm volatile("cp.async.bulk.shared::cluster.global.mbarrier::complete_tx::bytes [%0], [%1], %2, [%3];" ::"r"(dst), "l"(src), "r"(bytes), "r"(bar) : "memory");
}
__device__ __forceinline__ void bulk_s2g(void* dst, uint32_t src, int bytes) {
  asm volatile("cp.async.bulk.global.shared::cta.bulk_group [%0], [%1], %2;" ::"l"(dst), "r"(src), "r"(bytes) : "memory");
}
__device__ __forceinline__ void bulk_s2s(uint32_t dst, uint32_t src, int bytes, uint32_t bar) {
  asm volatile("cp.async.bulk.shared::cluster.shared::cta.mbarrier::complete_tx::bytes [%0], [%1], %2, [%3];" ::"r"(dst), "r"(src), "r"(bytes), "r"(bar) : "memory");
}
__device__ __forceinline__ void bulk_commit() { asm volatile("cp.async.bulk.commit_group;" ::: "memory"); }
__device__ __forceinline__ void bulk_wait0() { asm volatile("cp.async.bulk.wait_group 0;" ::: "memory"); }
__device__ __forceinline__ void l2_prefetch(const void* p, int bytes) { asm volatile("cp.async.bulk.prefetch.L2.global [%0], %1;" ::"l"(p), "r"(bytes) : "memory"); }
__device__ __forceinline__ void delay(uint32_t cycles) {
  uint32_t c0, c1;
  asm volatile("mov.u32 %0, %%clock;" : "=r"(c0));
  do { asm volatile("mov.u32 %0, %%clock;" : "=r"(c1)); } while (c1 - c0 < cycles);
}
__device__ __forceinline__ void prefetch_map(const CUtensorMap* m) { asm volatile("prefetch.tensormap [%0];" ::"l"(m) : "memory"); }

__device__ __forceinline__ void ldsm4(uint32_t* r, uint32_t a) { asm volatile("ldmatrix.sync.aligned.m8n8.x4.shared.b16 {%0,%1,%2,%3}, [%4];" : "=r"(r[0]), "=r"(r[1]), "=r"(r[2]), "=r"(r[3]) : "r"(a) : "memory"); }
__device__ __forceinline__ void stsm4(uint32_t a, uint32_t r0, uint32_t r1, uint32_t r2, uint32_t r3) { asm volatile("stmatrix.sync.aligned.m8n8.x4.shared.b16 [%0], {%1,%2,%3,%4};" ::"r"(a), "r"(r0), "r"(r1), "r"(r2), "r"(r3) : "memory"); }
__device__ __forceinline__ void stsm2(uint32_t a, uint32_t r0, uint32_t r1) { asm volatile("stmatrix.sync.aligned.m8n8.x2.shared.b16 [%0], {%1,%2};" ::"r"(a), "r"(r0), "r"(r1) : "memory"); }
__device__ __forceinline__ uint32_t pack2(float lo, float hi) { uint32_t r; asm("cvt.rn.bf16x2.f32 %0, %1, %2;" : "=r"(r) : "f"(hi), "f"(lo)); return r; }
__device__ __forceinline__ float bf_lo(uint32_t v) { return __uint_as_float(v << 16); }
__device__ __forceinline__ float bf_hi(uint32_t v) { return __uint_as_float(v & 0xffff0000u); }
__device__ __forceinline__ float rbf(float v) { return bf_lo(pack2(v, 0.f)); }
__device__ __forceinline__ uint32_t sub2(uint32_t a, uint32_t b) { uint32_t r; asm("sub.rn.bf16x2 %0, %1, %2;" : "=r"(r) : "r"(a), "r"(b)); return r; }
__device__ __forceinline__ uint32_t add2(uint32_t a, uint32_t b) { uint32_t r; asm("add.rn.bf16x2 %0, %1, %2;" : "=r"(r) : "r"(a), "r"(b)); return r; }
__device__ __forceinline__ uint32_t mul2(uint32_t a, uint32_t b) { uint32_t r; asm("mul.rn.bf16x2 %0, %1, %2;" : "=r"(r) : "r"(a), "r"(b)); return r; }
__device__ __forceinline__ float ex2(float v) { float r; asm("ex2.approx.ftz.f32 %0, %1;" : "=f"(r) : "f"(v)); return r; }
__device__ __forceinline__ float tanh_approx(float v) { float r; asm("tanh.approx.f32 %0, %1;" : "=f"(r) : "f"(v)); return r; }
__device__ __forceinline__ float sqrt_approx(float v) { float r; asm("sqrt.approx.ftz.f32 %0, %1;" : "=f"(r) : "f"(v)); return r; }
__device__ __forceinline__ float rcp(float v) { float r; asm("rcp.approx.ftz.f32 %0, %1;" : "=f"(r) : "f"(v)); return r; }
__device__ __forceinline__ void lds128v(uint32_t* v, uint32_t a) { asm volatile("ld.shared.v4.u32 {%0,%1,%2,%3}, [%4];" : "=r"(v[0]), "=r"(v[1]), "=r"(v[2]), "=r"(v[3]) : "r"(a) : "memory"); }
__device__ __forceinline__ void sts128(uint32_t a, uint4 v) { asm volatile("st.shared.v4.u32 [%0], {%1,%2,%3,%4};" ::"r"(a), "r"(v.x), "r"(v.y), "r"(v.z), "r"(v.w) : "memory"); }

__device__ __forceinline__ void wg_fence() { asm volatile("wgmma.fence.sync.aligned;" ::: "memory"); }
__device__ __forceinline__ void wg_commit() { asm volatile("wgmma.commit_group.sync.aligned;" ::: "memory"); }
template <int N> __device__ __forceinline__ void wg_wait() { asm volatile("wgmma.wait_group.sync.aligned %0;" ::"n"(N) : "memory"); }
template <int N> __device__ __forceinline__ void reg_fence(float* d) {
#pragma unroll
  for (int i = 0; i < N; i++) asm volatile("" : "+f"(d[i])::"memory");
}
template <int N> __device__ __forceinline__ void zero(float* d) {
#pragma unroll
  for (int i = 0; i < N; i++) d[i] = 0.f;
}
__device__ __forceinline__ uint64_t mkdesc(uint32_t addr, uint32_t lbo, uint32_t sbo, uint32_t sw) {
  return (uint64_t)((addr & 0x3FFFF) >> 4) | ((uint64_t)(lbo >> 4) << 16) | ((uint64_t)(sbo >> 4) << 32) | ((uint64_t)sw << 62);
}

__device__ __forceinline__ void wgmma_rs_n56(float* d, const uint32_t* a, uint64_t db, int sd) {
  asm volatile("{\n.reg .pred p;\nsetp.ne.b32 p, %33, 0;\nwgmma.mma_async.sync.aligned.m64n56k16.f32.bf16.bf16 {%0,%1,%2,%3,%4,%5,%6,%7,%8,%9,%10,%11,%12,%13,%14,%15,%16,%17,%18,%19,%20,%21,%22,%23,%24,%25,%26,%27}, {%28,%29,%30,%31}, %32, p, 1, 1, 1;\n}\n"
    : "+f"(d[0]),"+f"(d[1]),"+f"(d[2]),"+f"(d[3]),"+f"(d[4]),"+f"(d[5]),"+f"(d[6]),"+f"(d[7]),"+f"(d[8]),"+f"(d[9]),"+f"(d[10]),"+f"(d[11]),"+f"(d[12]),"+f"(d[13]),"+f"(d[14]),"+f"(d[15]),"+f"(d[16]),"+f"(d[17]),"+f"(d[18]),"+f"(d[19]),"+f"(d[20]),"+f"(d[21]),"+f"(d[22]),"+f"(d[23]),"+f"(d[24]),"+f"(d[25]),"+f"(d[26]),"+f"(d[27])
    : "r"(a[0]),"r"(a[1]),"r"(a[2]),"r"(a[3]),"l"(db),"r"(sd));
}
__device__ __forceinline__ void wgmma_rs_n64(float* d, const uint32_t* a, uint64_t db, int sd) {
  asm volatile("{\n.reg .pred p;\nsetp.ne.b32 p, %37, 0;\nwgmma.mma_async.sync.aligned.m64n64k16.f32.bf16.bf16 {%0,%1,%2,%3,%4,%5,%6,%7,%8,%9,%10,%11,%12,%13,%14,%15,%16,%17,%18,%19,%20,%21,%22,%23,%24,%25,%26,%27,%28,%29,%30,%31}, {%32,%33,%34,%35}, %36, p, 1, 1, 1;\n}\n"
    : "+f"(d[0]),"+f"(d[1]),"+f"(d[2]),"+f"(d[3]),"+f"(d[4]),"+f"(d[5]),"+f"(d[6]),"+f"(d[7]),"+f"(d[8]),"+f"(d[9]),"+f"(d[10]),"+f"(d[11]),"+f"(d[12]),"+f"(d[13]),"+f"(d[14]),"+f"(d[15]),"+f"(d[16]),"+f"(d[17]),"+f"(d[18]),"+f"(d[19]),"+f"(d[20]),"+f"(d[21]),"+f"(d[22]),"+f"(d[23]),"+f"(d[24]),"+f"(d[25]),"+f"(d[26]),"+f"(d[27]),"+f"(d[28]),"+f"(d[29]),"+f"(d[30]),"+f"(d[31])
    : "r"(a[0]),"r"(a[1]),"r"(a[2]),"r"(a[3]),"l"(db),"r"(sd));
}
__device__ __forceinline__ void wgmma_rs_n128(float* d, const uint32_t* a, uint64_t db, int sd) {
  asm volatile("{\n.reg .pred p;\nsetp.ne.b32 p, %69, 0;\nwgmma.mma_async.sync.aligned.m64n128k16.f32.bf16.bf16 {%0,%1,%2,%3,%4,%5,%6,%7,%8,%9,%10,%11,%12,%13,%14,%15,%16,%17,%18,%19,%20,%21,%22,%23,%24,%25,%26,%27,%28,%29,%30,%31,%32,%33,%34,%35,%36,%37,%38,%39,%40,%41,%42,%43,%44,%45,%46,%47,%48,%49,%50,%51,%52,%53,%54,%55,%56,%57,%58,%59,%60,%61,%62,%63}, {%64,%65,%66,%67}, %68, p, 1, 1, 1;\n}\n"
    : "+f"(d[0]),"+f"(d[1]),"+f"(d[2]),"+f"(d[3]),"+f"(d[4]),"+f"(d[5]),"+f"(d[6]),"+f"(d[7]),"+f"(d[8]),"+f"(d[9]),"+f"(d[10]),"+f"(d[11]),"+f"(d[12]),"+f"(d[13]),"+f"(d[14]),"+f"(d[15]),"+f"(d[16]),"+f"(d[17]),"+f"(d[18]),"+f"(d[19]),"+f"(d[20]),"+f"(d[21]),"+f"(d[22]),"+f"(d[23]),"+f"(d[24]),"+f"(d[25]),"+f"(d[26]),"+f"(d[27]),"+f"(d[28]),"+f"(d[29]),"+f"(d[30]),"+f"(d[31]),"+f"(d[32]),"+f"(d[33]),"+f"(d[34]),"+f"(d[35]),"+f"(d[36]),"+f"(d[37]),"+f"(d[38]),"+f"(d[39]),"+f"(d[40]),"+f"(d[41]),"+f"(d[42]),"+f"(d[43]),"+f"(d[44]),"+f"(d[45]),"+f"(d[46]),"+f"(d[47]),"+f"(d[48]),"+f"(d[49]),"+f"(d[50]),"+f"(d[51]),"+f"(d[52]),"+f"(d[53]),"+f"(d[54]),"+f"(d[55]),"+f"(d[56]),"+f"(d[57]),"+f"(d[58]),"+f"(d[59]),"+f"(d[60]),"+f"(d[61]),"+f"(d[62]),"+f"(d[63])
    : "r"(a[0]),"r"(a[1]),"r"(a[2]),"r"(a[3]),"l"(db),"r"(sd));
}
__device__ __forceinline__ void wgmma_ss_n112(float* d, uint64_t da, uint64_t db, int sd) {
  asm volatile("{\n.reg .pred p;\nsetp.ne.b32 p, %58, 0;\nwgmma.mma_async.sync.aligned.m64n112k16.f32.bf16.bf16 {%0,%1,%2,%3,%4,%5,%6,%7,%8,%9,%10,%11,%12,%13,%14,%15,%16,%17,%18,%19,%20,%21,%22,%23,%24,%25,%26,%27,%28,%29,%30,%31,%32,%33,%34,%35,%36,%37,%38,%39,%40,%41,%42,%43,%44,%45,%46,%47,%48,%49,%50,%51,%52,%53,%54,%55}, %56, %57, p, 1, 1, 0, 1;\n}\n"
    : "+f"(d[0]),"+f"(d[1]),"+f"(d[2]),"+f"(d[3]),"+f"(d[4]),"+f"(d[5]),"+f"(d[6]),"+f"(d[7]),"+f"(d[8]),"+f"(d[9]),"+f"(d[10]),"+f"(d[11]),"+f"(d[12]),"+f"(d[13]),"+f"(d[14]),"+f"(d[15]),"+f"(d[16]),"+f"(d[17]),"+f"(d[18]),"+f"(d[19]),"+f"(d[20]),"+f"(d[21]),"+f"(d[22]),"+f"(d[23]),"+f"(d[24]),"+f"(d[25]),"+f"(d[26]),"+f"(d[27]),"+f"(d[28]),"+f"(d[29]),"+f"(d[30]),"+f"(d[31]),"+f"(d[32]),"+f"(d[33]),"+f"(d[34]),"+f"(d[35]),"+f"(d[36]),"+f"(d[37]),"+f"(d[38]),"+f"(d[39]),"+f"(d[40]),"+f"(d[41]),"+f"(d[42]),"+f"(d[43]),"+f"(d[44]),"+f"(d[45]),"+f"(d[46]),"+f"(d[47]),"+f"(d[48]),"+f"(d[49]),"+f"(d[50]),"+f"(d[51]),"+f"(d[52]),"+f"(d[53]),"+f"(d[54]),"+f"(d[55])
    : "l"(da),"l"(db),"r"(sd));
}
__device__ __forceinline__ void wgmma_ss_n56(float* d, uint64_t da, uint64_t db, int sd) {
  asm volatile("{\n.reg .pred p;\nsetp.ne.b32 p, %30, 0;\nwgmma.mma_async.sync.aligned.m64n56k16.f32.bf16.bf16 {%0,%1,%2,%3,%4,%5,%6,%7,%8,%9,%10,%11,%12,%13,%14,%15,%16,%17,%18,%19,%20,%21,%22,%23,%24,%25,%26,%27}, %28, %29, p, 1, 1, 0, 1;\n}\n"
    : "+f"(d[0]),"+f"(d[1]),"+f"(d[2]),"+f"(d[3]),"+f"(d[4]),"+f"(d[5]),"+f"(d[6]),"+f"(d[7]),"+f"(d[8]),"+f"(d[9]),"+f"(d[10]),"+f"(d[11]),"+f"(d[12]),"+f"(d[13]),"+f"(d[14]),"+f"(d[15]),"+f"(d[16]),"+f"(d[17]),"+f"(d[18]),"+f"(d[19]),"+f"(d[20]),"+f"(d[21]),"+f"(d[22]),"+f"(d[23]),"+f"(d[24]),"+f"(d[25]),"+f"(d[26]),"+f"(d[27])
    : "l"(da),"l"(db),"r"(sd));
}
__device__ __forceinline__ void wgmma_ssk_n80(float* d, uint64_t da, uint64_t db, int sd) {
  asm volatile("{\n.reg .pred p;\nsetp.ne.b32 p, %42, 0;\nwgmma.mma_async.sync.aligned.m64n80k16.f32.bf16.bf16 {%0,%1,%2,%3,%4,%5,%6,%7,%8,%9,%10,%11,%12,%13,%14,%15,%16,%17,%18,%19,%20,%21,%22,%23,%24,%25,%26,%27,%28,%29,%30,%31,%32,%33,%34,%35,%36,%37,%38,%39}, %40, %41, p, 1, 1, 0, 0;\n}\n"
    : "+f"(d[0]),"+f"(d[1]),"+f"(d[2]),"+f"(d[3]),"+f"(d[4]),"+f"(d[5]),"+f"(d[6]),"+f"(d[7]),"+f"(d[8]),"+f"(d[9]),"+f"(d[10]),"+f"(d[11]),"+f"(d[12]),"+f"(d[13]),"+f"(d[14]),"+f"(d[15]),"+f"(d[16]),"+f"(d[17]),"+f"(d[18]),"+f"(d[19]),"+f"(d[20]),"+f"(d[21]),"+f"(d[22]),"+f"(d[23]),"+f"(d[24]),"+f"(d[25]),"+f"(d[26]),"+f"(d[27]),"+f"(d[28]),"+f"(d[29]),"+f"(d[30]),"+f"(d[31]),"+f"(d[32]),"+f"(d[33]),"+f"(d[34]),"+f"(d[35]),"+f"(d[36]),"+f"(d[37]),"+f"(d[38]),"+f"(d[39])
    : "l"(da),"l"(db),"r"(sd));
}
__device__ __forceinline__ void wgmma_rs_n32(float* d, const uint32_t* a, uint64_t db, int sd) {
  asm volatile("{\n.reg .pred p;\nsetp.ne.b32 p, %21, 0;\nwgmma.mma_async.sync.aligned.m64n32k16.f32.bf16.bf16 {%0,%1,%2,%3,%4,%5,%6,%7,%8,%9,%10,%11,%12,%13,%14,%15}, {%16,%17,%18,%19}, %20, p, 1, 1, 1;\n}\n"
    : "+f"(d[0]),"+f"(d[1]),"+f"(d[2]),"+f"(d[3]),"+f"(d[4]),"+f"(d[5]),"+f"(d[6]),"+f"(d[7]),"+f"(d[8]),"+f"(d[9]),"+f"(d[10]),"+f"(d[11]),"+f"(d[12]),"+f"(d[13]),"+f"(d[14]),"+f"(d[15])
    : "r"(a[0]),"r"(a[1]),"r"(a[2]),"r"(a[3]),"l"(db),"r"(sd));
}

constexpr float LOG2E = 1.4426950408889634f;

__device__ __forceinline__ float swiglu(float g, float u, float hr) {
  const float z = g * hr, w = (u * hr) * z;
  return fmaf(w, tanh_approx(z), w);
}
__device__ __forceinline__ uint32_t fma2(uint32_t a, uint32_t b, uint32_t c) { uint32_t r; asm("fma.rn.bf16x2 %0, %1, %2, %3;" : "=r"(r) : "r"(a), "r"(b), "r"(c)); return r; }
__device__ __forceinline__ uint32_t gate2(float a0, float a1, uint32_t pv) {
  const float z0 = a0 + bf_lo(pv), z1 = a1 + bf_hi(pv);
  return pack2(fmaf(z0, tanh_approx(z0), z0), fmaf(z1, tanh_approx(z1), z1));
}

__device__ __forceinline__ void mma16(float* c, const uint32_t* a, uint32_t b0, uint32_t b1) {
  asm volatile("mma.sync.aligned.m16n8k16.row.col.f32.bf16.bf16.f32 {%0,%1,%2,%3}, {%4,%5,%6,%7}, {%8,%9}, {%0,%1,%2,%3};"
      : "+f"(c[0]), "+f"(c[1]), "+f"(c[2]), "+f"(c[3]) : "r"(a[0]), "r"(a[1]), "r"(a[2]), "r"(a[3]), "r"(b0), "r"(b1));
}
__device__ __forceinline__ void mma8(float* c, const uint32_t* a, uint32_t b) {
  asm volatile("mma.sync.aligned.m16n8k8.row.col.f32.bf16.bf16.f32 {%0,%1,%2,%3}, {%4,%5}, {%6}, {%0,%1,%2,%3};"
      : "+f"(c[0]), "+f"(c[1]), "+f"(c[2]), "+f"(c[3]) : "r"(a[0]), "r"(a[1]), "r"(b));
}
__device__ __forceinline__ void bar7(uint32_t dep) {
  asm volatile("{.reg .pred p; setp.eq.u32 p, %0, 0; bar.red.or.pred p, 7, 256, p;}" ::"r"(dep) : "memory");
}
__device__ __forceinline__ float stdev(float mean, float sq) {
  return rbf(sqrt_approx(rbf(rbf(fmaxf(fmaf(-mean, mean, sq * (1.f / D_)), 0.f)) + 1e-5f)));
}

struct Ring {
  uint32_t st, ph;
  __device__ __forceinline__ void next() { if (++st == NST) { st = 0; ph ^= 1; } }
};

__global__ void __cluster_dims__(2, 1, 1) __launch_bounds__(512, 1) fused_kernel(Scratch* __restrict__ gs, uint4* __restrict__ out, const uint4* __restrict__ x_in, const uint4* __restrict__ wqkv_in, const __grid_constant__ Params p) {
  extern __shared__ __align__(1024) uint8_t smem[];
  const uint32_t sb = s2u(smem);
  const uint32_t bars = sb + OFF_BAR;
  const int tid = threadIdx.x, warp = __shfl_sync(~0u, tid >> 5, 0), lane = tid & 31;
  const int rank = blockIdx.x & 1, cid = blockIdx.x >> 1;
  if (tid == 0) { TG(0); TS(1); }
  if (warp < 12) asm volatile("barrier.cluster.arrive.relaxed.aligned;" ::: "memory");
#define BAR(i) (bars + 8 * (i))
  const uint4* xp = x_in + ((blockIdx.x & 120) + blockIdx.x) * 448;
  if (tid == 256) {
    l2_prefetch(xp, 7168);
    delay(PD1);
    l2_prefetch(xp + 3584, 7168);
    delay(PD2);
    if (blockIdx.x < 112) {
#pragma unroll 1
      for (int i = 0; i < 4; i++) l2_prefetch(wqkv_in + (blockIdx.x + 112 * i) * 168 + 56, 1792);
    }
  }
  int grp, j;
  if (cid < 4) { grp = 0; j = 4 + cid; }
  else if (cid < 36) { grp = (cid - 4) & 7; j = (cid - 4) >> 3; }
  else { j = ((cid - 36) * 37) >> 8; grp = 1 + (cid - 36) - 7 * j; j += 4; }
  const int tb = 2 * grp + rank;
  const int T2 = 2 * grp + (j >> 2);
  const int qn = j & 3;
  const int wg = warp >> 2;
  if (warp < 12) {
  if (warp < 8) {
    const uint32_t xs = sb + (wg == 0 ? OFF_K : 7 * STAGE);
    {
      const int w = warp & 3;
      const uint32_t b0 = BAR(B_X + wg * 7 + w);
      if (lane == 0) {
        mbar_init(b0, 1);
        if (w < 3) mbar_init(b0 + 32, 1);
        fence_async_smem();
        mbar_expect(b0, 8192);
        if (w < 3) mbar_expect(b0 + 32, 8192);
      }
      if (wg == 1) asm volatile("bar.sync 4, 256;" ::: "memory");
      if (lane == 0) {
        tma2d(xs + w * 8192, &p.xm, b0, w * 64, tb * 128 + wg * 64);
        if (w < 3) tma2d(xs + (w + 4) * 8192 + (warp == 6 ? 57344 : 0), &p.xm, b0 + 32, (w + 4) * 64, tb * 128 + wg * 64);
      }
      TSW(2 + wg);
      if (wg == 0) asm volatile("bar.sync 4, 256;" ::: "memory");
    }
    asm volatile("barrier.cluster.wait.acquire.aligned;" ::: "memory");
    asm volatile("setmaxnreg.inc.sync.aligned.u32 208;");
    const int g = lane >> 2, q = lane & 3;
    uint32_t a[112];
    uint32_t m0, m1;
    float mu0, mu1, k0, k1;
    {
      const uint32_t xa = xs + ((warp & 3) * 16 + (lane & 15)) * 128;
      float sq[4][4], sum[2][4];
      zero<16>(&sq[0][0]); zero<8>(&sum[0][0]);
#pragma unroll
      for (int kt = 0; kt < 8; kt++) {
        if (kt < 7) {
          mbar_wait(BAR(B_X + wg * 7 + kt), 0);
          if (kt == 0) TSW(6 + wg);
          if (kt == 6) TSW(8 + wg);
          const uint32_t xk = xa + kt * 8192 + ((kt == 6 && wg == 1) ? 57344 : 0);
#pragma unroll
          for (int ks = 0; ks < 4; ks++) ldsm4(&a[16 * kt + 4 * ks], xk + (((2 * ks + (lane >> 4)) ^ (lane & 7)) << 4));
        }
        if (kt > 0) {
#pragma unroll
          for (int ks = 0; ks < 4; ks++) {
            const uint32_t* f = &a[16 * kt - 16 + 4 * ks];
            mma16(sum[ks & 1], f, 0x3f803f80u, 0x3f803f80u);
            mma8(sq[0], f, f[0]); mma8(sq[1], f, f[1]); mma8(sq[2], f + 2, f[2]); mma8(sq[3], f + 2, f[3]);
          }
        }
      }
      if (lane < 2) mbar_arrive_cluster(mapa(BAR(B_XFREE + wg), lane));
      k0 = (g & 1) ? sq[0][1] + sq[2][1] : sq[0][0] + sq[2][0];
      k1 = (g & 1) ? sq[1][3] + sq[3][3] : sq[1][2] + sq[3][2];
      if (wg == 1) bar7(__float_as_uint(k0) ^ __float_as_uint(k1));
      mu0 = (sum[0][0] + sum[1][0]) * (1.f / D_); mu1 = (sum[0][2] + sum[1][2]) * (1.f / D_);
      m0 = pack2(mu0, mu0); m1 = pack2(mu1, mu1);
#pragma unroll
      for (int i = 0; i < 16; i++) a[i] = sub2(a[i], (i & 1) ? m1 : m0);
      k0 = __shfl_sync(~0u, k0, (lane & 28) + (g >> 1)); k1 = __shfl_sync(~0u, k1, (lane & 28) + (g >> 1));
      TSW(4 + wg);
    }
    const bool rel = (lane == 0) && ((warp & 3) < 2);
    uint32_t rel_base = mapa(bars, rank ^ (warp & 1)) + 8 * B_EMPTY;
    const uint64_t dB128 = mkdesc(sb, 8192, 1024, 1);
    const uint64_t dW = dB128 + (j & 1);
    float rs0, rs1;

    {
      float accK[28], accV[28];
      mbar_wait(BAR(B_FULL), 0);
      if (wg == 0) {
        uint32_t d = __float_as_uint(k0) | __float_as_uint(k1);
#pragma unroll
        for (int i = 0; i < 16; i++) d |= a[i];
        bar7(d);
      } else {
        asm volatile("bar.sync 1, 256;" ::: "memory");
      }
#pragma unroll
      for (int kt = 0; kt < 7; kt++) {
        if (kt > 0) SW(BAR(B_FULL + kt), 0);
        TSW(70 + 2 * kt + wg);
        wg_fence();
#pragma unroll
        for (int ks = 0; ks < 4; ks++) {
          wgmma_rs_n56(accK, &a[(kt * 4 + ks) * 4], dW + (kt * 1024 + ks * 128), kt | ks);
          wgmma_rs_n56(accV, &a[(kt * 4 + ks) * 4], dW + (kt * 1024 + 512 + ks * 128), kt | ks);
        }
        wg_commit();
        if (kt == LAG0 && wg == 0) asm volatile("bar.arrive 1, 256;" ::: "memory");
        if (kt == LAGB && wg == 1) asm volatile("bar.arrive 5, 256;" ::: "memory");
        if (kt < 6) {
#pragma unroll
          for (int i = (kt + 1) * 16; i < (kt + 2) * 16; i++) asm volatile("sub.rn.bf16x2 %0, %0, %1;" : "+r"(a[i]) : "r"((i & 1) ? m1 : m0));
        }
        if (kt > 0) { wg_wait<1>(); if (rel) mbar_arrive_cluster(rel_base + 8 * (kt - 1)); }
      }
      rs0 = rcp(stdev(mu0, k0)); rs1 = rcp(stdev(mu1, k1));
      asm volatile("" : "+f"(rs0), "+f"(rs1));
      wg_wait<0>();
      reg_fence<28>(accK); reg_fence<28>(accV);
      if (rel) mbar_arrive_cluster(rel_base + 8 * 6);
      mbar_wait(BAR(B_XFREE), 0);
      TSW(10 + wg); SDUMP(70 + wg);
      const uint32_t ka = sb + OFF_K + (lane >> 4) * KVB + (2 + 2 * warp + ((lane >> 3) & 1)) * 896 + (lane & 7) * 16;
#pragma unroll
      for (int c = 0; c < 7; c++)
        stsm4(ka + c * 128, pack2(accK[4 * c] * rs0, accK[4 * c + 1] * rs0), pack2(accK[4 * c + 2] * rs1, accK[4 * c + 3] * rs1),
              pack2(accV[4 * c] * rs0, accV[4 * c + 1] * rs0), pack2(accV[4 * c + 2] * rs1, accV[4 * c + 3] * rs1));
      fence_async_smem();
      __syncwarp();
      if (lane == 0) mbar_arrive(BAR(B_KV));
      TSW(12 + wg);
    }
    const float hr0 = 0.5f * rs0, hr1 = 0.5f * rs1;
    const uint32_t tile_off = (lane >> 4) * 1024 + ((warp & 3) * 16 + (lane & 15)) * 16;
    const uint32_t hs_st = sb + OFF_HS + wg * 8192 + tile_off;
    const int bar_mine = 5 - 4 * wg, bar_other = 1 + 4 * wg;

    {
      const uint64_t dB64 = mkdesc(sb + 8192, 4096, 512, 2);
      float accQ[28], accG[32];
      asm volatile("bar.sync %0, 256;" ::"r"(bar_mine) : "memory");
#pragma unroll
      for (int kt = 0; kt < 7; kt++) {
        const int st = (7 + kt) % 10;
        SW(BAR(B_FULL + st), kt >= 3);
        if (kt == 0) TSW(14 + wg);
        wg_fence();
#pragma unroll
        for (int ks = 0; ks < 4; ks++) {
          wgmma_rs_n56(accQ, &a[(kt * 4 + ks) * 4], dW + (st * 1024 + ks * 128), kt | ks);
          wgmma_rs_n64(accG, &a[(kt * 4 + ks) * 4], dB64 + (st * 1024 + ks * 64), kt | ks);
        }
        wg_commit();
        if (kt == LAGA) asm volatile("bar.arrive %0, 256;" ::"r"(bar_other) : "memory");
        if (kt > 0) { wg_wait<1>(); if (rel) mbar_arrive_cluster(rel_base + 8 * ((6 + kt) % 10)); }
      }
      wg_wait<0>();
      reg_fence<28>(accQ); reg_fence<32>(accG);
      if (rel) mbar_arrive_cluster(rel_base + 8 * 3);
      mbar_wait(BAR(B_STG), 0);
      TSW(16 + wg); SDUMP(72 + wg);
      const uint32_t qa = hs_st - (OFF_HS - OFF_Q);
      uint32_t qp[14];
#pragma unroll
      for (int c = 0; c < 7; c++) { qp[2 * c] = pack2(accQ[4 * c] * rs0, accQ[4 * c + 1] * rs0); qp[2 * c + 1] = pack2(accQ[4 * c + 2] * rs1, accQ[4 * c + 3] * rs1); }
      stsm4(qa, qp[0], qp[1], qp[2], qp[3]);
      stsm4(qa + 2048, qp[4], qp[5], q < 2 ? qp[6] : 0u, q < 2 ? qp[7] : 0u);
      stsm4(qa + 4096, q < 2 ? 0u : qp[6], q < 2 ? 0u : qp[7], qp[8], qp[9]);
      stsm4(qa + 6144, qp[10], qp[11], qp[12], qp[13]);
#pragma unroll
      for (int c = 0; c < 2; c++) {
        uint32_t hp[4];
#pragma unroll
        for (int e = 0; e < 2; e++) {
          const float* gg = &accG[8 * c + 4 * e]; const float* uu = &accG[16 + 8 * c + 4 * e];
          hp[2 * e] = pack2(swiglu(gg[0], uu[0], hr0), swiglu(gg[1], uu[1], hr0));
          hp[2 * e + 1] = pack2(swiglu(gg[2], uu[2], hr1), swiglu(gg[3], uu[3], hr1));
        }
        stsm4(hs_st + c * 2048, hp[0], hp[1], hp[2], hp[3]);
      }
      fence_async_smem();
      __syncwarp();
      if (lane < 2) mbar_arrive(BAR(B_Q + wg + 2 * lane));
      TSW(18 + wg);
    }

    Ring rg{4, 1};
#pragma unroll 1
    for (int c3 = 0; c3 < 3; c3++) {
      float acc[64];
      if (c3 == 2) rel_base = mapa(bars, rank) + 8 * B_EMPTY;
      mbar_wait(BAR(B_FULL + rg.st), rg.ph);
      asm volatile("bar.sync %0, 256;" ::"r"(bar_mine) : "memory");
      uint32_t prev = 0;
#pragma unroll
      for (int kt = 0; kt < 7; kt++) {
        if (kt > 0) SW(BAR(B_FULL + rg.st), rg.ph);
        if (kt == 0) TSW(20 + 6 * c3 + wg);
        const uint64_t db = dB128 + (uint64_t)(rg.st * (STAGE >> 4));
        wg_fence();
#pragma unroll
        for (int ks = 0; ks < 4; ks++) wgmma_rs_n128(acc, &a[(kt * 4 + ks) * 4], db + ks * 128, kt | ks);
        wg_commit();
        if (kt == LAGP4 || kt == LAGA) { if ((kt == LAGP4) == (c3 == 2 && wg == 0)) asm volatile("bar.arrive %0, 256;" ::"r"(bar_other) : "memory"); }
        if (kt > 0) { wg_wait<1>(); if (rel) mbar_arrive_cluster(rel_base + 8 * prev); }
        prev = rg.st; rg.next();
      }
      wg_wait<0>();
      reg_fence<64>(acc);
      if (rel) mbar_arrive_cluster(rel_base + 8 * prev);
      mbar_wait(BAR(B_HFREE + wg), c3 & 1);
      TSW(22 + 6 * c3 + wg); SDUMP(74 + 2 * c3 + wg);
#pragma unroll
      for (int c = 0; c < 4; c++) {
        uint32_t hp[4];
#pragma unroll
        for (int e = 0; e < 4; e++) { const int i = 8 * c + 2 * e; const float hr = (i & 2) ? hr1 : hr0; hp[e] = pack2(swiglu(acc[i], acc[32 + i], hr), swiglu(acc[i + 1], acc[33 + i], hr)); }
        stsm4(hs_st + c * 2048, hp[0], hp[1], hp[2], hp[3]);
      }
      fence_async_smem();
      __syncwarp();
      if (lane == 0) mbar_arrive(BAR(B_H + wg));
      TSW(24 + 6 * c3 + wg);
    }

    uint64_t dA = mkdesc(sb, 1024, 128, 0);
    const uint64_t dBn = mkdesc(sb, 128, 1024, 0);
    uint64_t dWo = dBn + (OFF_WOB >> 4);
    const bool rel2 = (tid & 127) == 0;
    float dacc[56], sacc[28];
    uint32_t xr[14];
    auto wo_step = [&](int k, int slot) { wgmma_ss_n56(sacc, dA + (((slot + (k >> 3)) % 10) * 1024 + (k & 7) * 128), dWo + ((k >> 2) * 448 + (k & 3) * 16), k); };
    auto load_x = [&](int slot) {
      const uint32_t xra = sb + slot * STAGE + 8192 + ((warp & 3) * 16 + (lane & 15)) * 112 + (lane >> 4) * 16;
#pragma unroll
      for (int c = 0; c < 3; c++) ldsm4(&xr[4 * c], xra + c * 32);
      asm volatile("ldmatrix.sync.aligned.m8n8.x2.shared.b16 {%0,%1}, [%2];" : "=r"(xr[12]), "=r"(xr[13]) : "r"(xra + 96) : "memory");
    };
    mbar_wait(BAR(B_WOB), 0);
    if (wg == 0) {
      mbar_wait(BAR(B_FULL2), 0);
      asm volatile("bar.sync 5, 256;" ::: "memory");
      TSW(112);
      wg_fence();
#pragma unroll
      for (int k = 0; k < 16; k++) wo_step(k, 5);
      wg_commit();
      mbar_wait(BAR(B_FULL2 + 1), 0);
      load_x(8);
      wg_fence();
      wo_step(16, 5);
      wg_commit();
      wg_wait<1>();
      if (rel2) mbar_arrive(BAR(B_EMPTY2));
      asm volatile("bar.arrive 1, 256;" ::: "memory");
#pragma unroll
      for (int k = 17; k < 28; k++) wo_step(k, 5);
      wg_commit();
      asm volatile("{.reg .pred p; setp.ne.u32 p, %1, 1; @p st.shared.u32 [%1], %0;}" ::"r"(xr[0] ^ xr[4] ^ xr[8] ^ xr[12]), "r"(gridDim.y) : "memory");
    } else {
      asm volatile("bar.sync 1, 256;" ::: "memory");
    }
    int pr = 2, ph = 0, prev = 1;
#pragma unroll 1
    for (int kt = 0; kt < 14; kt++) {
      SW(BAR(B_FULL2 + pr), ph);
      TSW(84 + 2 * kt + wg);
      const uint64_t da = dA + (uint32_t)((pr < 3 ? 5 + 2 * pr : 2 * pr - 5) * 1024 + wg * 512);
      const uint64_t db = dBn + (uint32_t)((pr < 2 ? 6 + 2 * pr : 2 * pr - 4) * 1024);
      if (kt == LEAD && wg == 1) asm volatile("bar.sync 6, 256;" ::: "memory");
      wg_fence();
#pragma unroll
      for (int ks = 0; ks < 4; ks++) wgmma_ss_n112(dacc, da + ks * 128, db + ks * 16, kt | ks);
      wg_commit();
      if (kt == 13 && wg == 0) asm volatile("bar.arrive 6, 256;" ::: "memory");
      wg_wait<1>();
      if (rel2 && kt >= wg) mbar_arrive(BAR(B_EMPTY2 + prev));
      prev = pr;
      if (++pr == 5) { pr = 0; ph ^= 1; }
    }
    {
      const uint32_t part = sb + OFF_PART + warp * 1792;
      const uint32_t dst = mapa(part, rank ^ 1) + lane * 16, pb = mapa(BAR(B_PART + 2 * wg), rank ^ 1);
      const uint32_t aLo = (uint32_t)dA, bLo = (uint32_t)dWo;
      auto wo1 = [&](int k) { wgmma_ss_n56(sacc, (dA >> 32 << 32) | (aLo + (((7 + (k >> 3)) % 10) * 1024 + (k & 7) * 128)), (dWo >> 32 << 32) | (bLo + ((k >> 2) * 448 + (k & 3) * 16)), k); };
      mbar_wait(BAR(B_PFREE), 0);
      wg_wait<0>();
      reg_fence<56>(dacc);
      TSW(38 + wg); SDUMP(80 + wg);
#pragma unroll
      for (int i = 0; i < 4; i++) {
        const float* d = &dacc[28 + 8 * i];
        if (i < 3)
          asm volatile("st.async.shared::cluster.mbarrier::complete_tx::bytes.v4.b32 [%0], {%1,%2,%3,%4}, [%5];"
                       ::"r"(dst + i * 512), "r"(pack2(d[0], d[1])), "r"(pack2(d[2], d[3])), "r"(pack2(d[4], d[5])), "r"(pack2(d[6], d[7])), "r"(pb + (i >> 1) * 8) : "memory");
        else
          asm volatile("st.async.shared::cluster.mbarrier::complete_tx::bytes.v2.b32 [%0], {%1,%2}, [%3];"
                       ::"r"(dst + 1536 - lane * 8), "r"(pack2(d[0], d[1])), "r"(pack2(d[2], d[3])), "r"(pb + 8) : "memory");
      }
      TSW(40 + wg);
      if (wg == 1) {
        mbar_wait(BAR(B_FULL2 + 1), 1);
        TSW(113);
        wg_fence();
#pragma unroll
        for (int k = 0; k < 16; k++) wo1(k);
        mbar_wait(BAR(B_FULL2 + 2), 1);
        wg_fence();
#pragma unroll
        for (int k = 16; k < 28; k++) wo1(k);
        wg_commit();
        TSW(117);
      }
      const uint32_t pl = part + lane * 16, oa = part + (lane & 15) * 112 + (lane >> 4) * 16;
      uint32_t gp[14];
      mbar_wait(BAR(B_PART + 2 * wg), 0);
      TSW(120 + wg);
      lds128v(&gp[0], pl); lds128v(&gp[4], pl + 512);
#pragma unroll
      for (int i = 0; i < 8; i++) gp[i] = gate2(dacc[2 * i], dacc[2 * i + 1], gp[i]);
      mbar_wait(BAR(B_PART + 2 * wg + 1), 0);
      TSW(118 + wg);
      lds128v(&gp[8], pl + 1024);
      asm volatile("ld.shared.v2.u32 {%0,%1}, [%2];" : "=r"(gp[12]), "=r"(gp[13]) : "r"(part + 1536 + lane * 8) : "memory");
#pragma unroll
      for (int i = 8; i < 14; i++) gp[i] = gate2(dacc[2 * i], dacc[2 * i + 1], gp[i]);
      if (wg == 1) {
        const uint32_t xra = oa + (8192 - OFF_PART - 4 * 1792);
#pragma unroll
        for (int c = 0; c < 3; c++) ldsm4(&xr[4 * c], xra + c * 32);
        asm volatile("ldmatrix.sync.aligned.m8n8.x2.shared.b16 {%0,%1}, [%2];" : "=r"(xr[12]), "=r"(xr[13]) : "r"(xra + 96) : "memory");
      }
      if (lane == 0) mbar_arrive(BAR(B_DONE));
      wg_wait<0>();
      reg_fence<28>(sacc);
      __syncwarp();
      TSW(42 + wg);
#pragma unroll
      for (int c = 0; c < 14; c++) xr[c] = fma2(pack2(sacc[2 * c], sacc[2 * c + 1]), gp[c], xr[c]);
#pragma unroll
      for (int c = 0; c < 3; c++) stsm4(oa + c * 32, xr[4 * c], xr[4 * c + 1], xr[4 * c + 2], xr[4 * c + 3]);
      stsm2(oa + 96, xr[12], xr[13]);
      __syncwarp();
      uint32_t y[16];
#pragma unroll
      for (int i = 0; i < 4; i++) lds128v(&y[4 * i], pl + i * 512);
#pragma unroll
      for (int i = 0; i < 4; i++) {
        const int c = lane + 32 * i;
        asm volatile("{.reg .pred p; setp.lt.u32 p, %5, 16; @p st.global.v4.u32 [%0], {%1,%2,%3,%4};}"
                     ::"l"(out + ((T2 * 128 + warp * 16) * 56 + qn * 14 + rank * 7 + ((c * 147) >> 10) * 49 + c)), "r"(y[4 * i]), "r"(y[4 * i + 1]), "r"(y[4 * i + 2]), "r"(y[4 * i + 3]), "r"(i < 3 ? 0 : lane) : "memory");
      }
    }
    TSW(44 + wg);
    FIN;
  } else {
    asm volatile("setmaxnreg.dec.sync.aligned.u32 72;");
    asm volatile("barrier.cluster.wait.acquire.aligned;" ::: "memory");
    const int w = warp & 3, g = lane >> 2, q = lane & 3;
    {
      const bool two = blockIdx.x < 12;
      if (tid == 256) {
        const int u = blockIdx.x;
        prefetch_map(&p.wdm); prefetch_map(&p.wom);
        mbar_wait(BAR(B_XFREE), 0);
        mbar_wait(BAR(B_XFREE + 1), 0);
        TS(124);
        mbar_expect(BAR(B_RT), two ? 28672 : 14336);
        tma2d(sb + OFF_Q, u < 112 ? &p.wdm : &p.wom, BAR(B_RT), (u & 3) * 112, ((u >> 2) - (u < 112 ? 0 : 28)) * 64);
        if (two) tma2d(sb + OFF_Q + 14336, &p.wom, BAR(B_RT), (u & 3) * 112, ((u >> 2) + 4) * 64);
      }
      const int row = tid & 63, c0 = ((tid >> 6) ^ (tid >> 2)) & 1;
      mbar_wait(BAR(B_RT), 0);
      TSW(125);
#pragma unroll 1
      for (uint32_t stg = sb + OFF_Q; stg <= sb + OFF_Q + two * 14336; stg += 14336) {
        uint32_t v[28];
#pragma unroll
        for (int i = 0; i < 7; i++) lds128v(&v[4 * i], stg + row * 224 + c0 * 16 + i * 32);
        asm volatile("bar.sync 2, 128;" ::: "memory");
#pragma unroll
        for (int i = 0; i < 7; i++) sts128(stg + c0 * 1024 + row * 16 + i * 2048, make_uint4(v[4 * i], v[4 * i + 1], v[4 * i + 2], v[4 * i + 3]));
      }
      fence_async_smem();
      asm volatile("bar.sync 2, 128;" ::: "memory");
      TSW(51);
      if (warp == 8) {
        const int u = blockIdx.x + (lane >> 1) * 128, e = lane & 1;
        if (u < 140) {
          uint4* dst = u < 112 ? gs->wd + ((u & 3) * 28 + (u >> 2)) * 896 + (e ^ (u >= 56)) * 448 : gs->wo + (2 * (u & 3) + e) * 3136 + ((u >> 2) - 28) * 448;
          bulk_s2g(dst, sb + OFF_Q + lane * 7168, 7168);
          bulk_commit();
        }
        asm volatile("cp.async.bulk.wait_group.read 0;" ::: "memory");
        __syncwarp();
        if (lane == 0) { mbar_arrive(BAR(B_STG)); TS(68); }
        bulk_wait0();
        __syncwarp();
        if (lane == 0) { flag_add(&gs->flag[F_W * 8]); TS(67); }
      }
    }
    const int par = g & 1;
    const float sl2 = 0.1889822365046136f * LOG2E;
    uint32_t o3a = 0, o3b = 0;
    mbar_wait(BAR(B_KV), 0);
    mbar_wait(BAR(B_HALO), 0);
    if (rank == 1 && tid == 256) mbar_arrive_cluster(mapa(BAR(B_KVFREE), 0));
#pragma unroll 1
    for (int it = 0; it < 4; it++) {
      const int mt = it >> 1, hh = it & 1;
      mbar_wait(BAR(B_Q + mt), 0);
      if (it == 3 && tid == 256) { bulk_wait0(); flag_add(&gs->flag[(F_O + 2 * tb) * 8]); }
      if (hh == 0) TSW(46 + 2 * mt);
      const uint64_t dQ = mkdesc(sb + OFF_Q, 1024, 128, 0) + (uint64_t)(mt * 512 + hh * 256);
      const uint64_t dK = mkdesc(sb + OFF_K, 128, 896, 0) + (uint64_t)(mt * 448 + hh * 24);
      const uint64_t dV = mkdesc(sb + OFF_V, 896, 128, 0) + (uint64_t)(mt * 448 + hh * 24);
      const int jmin = 16 - (tb * 128 + mt * 64 + w * 16);
      float s[40];
      wg_fence();
      wgmma_ssk_n80(s, dQ, dK, 0);
      wgmma_ssk_n80(s, dQ + 128, dK + 16, 1);
      wg_commit();
      wg_wait<0>();
      reg_fence<40>(s);
      float u[20], v[12], l[8];
#pragma unroll
      for (int i = 0; i < 20; i++) u[i] = par ? s[2 * i + 1] : s[2 * i];
#pragma unroll
      for (int i = 0; i < 12; i++) v[i] = (w & 2) ? u[i + 8] : u[i];
      float m0 = -INFINITY, m1 = -INFINITY;
#pragma unroll
      for (int n = 0; n < 4; n++) {
        const int jj = 8 * n + 2 * q + par;
        const uint32_t d0 = g + 16 - jj, d1 = d0 + 8;
        l[2 * n] = (n < 3 && jj >= jmin && d0 <= 14) ? ((w & 1) ? v[2 * n + 4] : v[2 * n]) : -INFINITY;
        l[2 * n + 1] = (n > 0 && jj >= jmin && d1 <= 14) ? ((w & 1) ? v[2 * n + 5] : v[2 * n + 1]) : -INFINITY;
        m0 = fmaxf(m0, l[2 * n]); m1 = fmaxf(m1, l[2 * n + 1]);
      }
      m0 = fmaxf(m0, __shfl_xor_sync(~0u, m0, 1)); m1 = fmaxf(m1, __shfl_xor_sync(~0u, m1, 1));
      m0 = fmaxf(m0, __shfl_xor_sync(~0u, m0, 2)); m1 = fmaxf(m1, __shfl_xor_sync(~0u, m1, 2));
      float z0 = 0.f, z1 = 0.f;
#pragma unroll
      for (int n = 0; n < 4; n++) {
        l[2 * n] = n < 3 ? ex2((l[2 * n] - m0) * sl2) : 0.f; l[2 * n + 1] = n > 0 ? ex2((l[2 * n + 1] - m1) * sl2) : 0.f;
        z0 += l[2 * n]; z1 += l[2 * n + 1];
      }
      z0 += __shfl_xor_sync(~0u, z0, 1); z1 += __shfl_xor_sync(~0u, z1, 1);
      z0 += __shfl_xor_sync(~0u, z0, 2); z1 += __shfl_xor_sync(~0u, z1, 2);
      const float i0 = rcp(z0), i1 = rcp(z1);
      uint32_t pf[8];
#pragma unroll
      for (int i = 0; i < 8; i++) pf[i] = (i == 1 || i == 6) ? 0u : pack2(l[i] * ((i & 1) ? i1 : i0), 0.f) << (16 * par);
      uint32_t pa[5][4];
#pragma unroll
      for (int k = 0; k < 5; k++)
#pragma unroll
        for (int r = 0; r < 4; r++) pa[k][r] = (k < 4 && k == w) ? pf[r] : ((k > 0 && k == w + 1) ? pf[4 + r] : 0u);
      float o[16];
      wg_fence();
#pragma unroll
      for (int k = 0; k < 5; k++) wgmma_rs_n32(o, pa[k], dV + k * 112, k);
      wg_commit();
      wg_wait<0>();
      reg_fence<16>(o);
      const uint32_t qa = sb + OFF_Q + mt * 8192 + hh * 3072 + (lane >> 4) * 1024 + (w * 16 + (lane & 15)) * 16;
      const bool keep = hh && q < 2;
      stsm4(qa, keep ? o3a : pack2(o[0], o[1]), keep ? o3b : pack2(o[2], o[3]), pack2(o[4], o[5]), pack2(o[6], o[7]));
      o3a = pack2(o[12], o[13]); o3b = pack2(o[14], o[15]);
      stsm4(qa + 2048, pack2(o[8], o[9]), pack2(o[10], o[11]), o3a, o3b);
      if (hh) {
        fence_async_smem();
        asm volatile("bar.sync 2, 128;" ::: "memory");
        if (tid == 256) {
          bulk_s2g(gs->o + ((tb * 2 + mt) * 56 + 7 * j) * 64, sb + OFF_Q + mt * 8192, 7168);
          bulk_commit();
        }
        TSW(47 + 2 * mt);
      }
    }
    if (lane != 0) return;
    if (warp == 8 || warp == 11) {
      const int skip = warp == 8 ? 40448 : 0;
      mbar_wait(BAR(B_WOK), 0);
      mbar_wait(BAR(B_KVFREE), 0);
      asm volatile("cp.async.bulk.wait_group.read 0;" ::: "memory");
      if (warp == 8) mbar_expect(BAR(B_WOB), 50176);
      bulk_g2s(sb + OFF_WOB + skip, gs->wo + (2 * qn + rank) * 3136 + (skip >> 4), warp == 8 ? 50176 - skip : 40448, BAR(B_WOB));
      if (warp == 8) {
        bulk_wait0();
        TS(50);
        flag_add(&gs->flag[(F_O + 2 * tb + 1) * 8]);
        mbar_arrive(BAR(B_DONE));
      }
    }
  }
  } else {
    asm volatile("setmaxnreg.dec.sync.aligned.u32 24;");
    if (lane == 0) {
      if (warp == 12) {
        prefetch_map(&p.wqkv);
#pragma unroll
        for (int i = 0; i < B_PART; i++) mbar_init(BAR(i), 1);
        mbar_init(BAR(B_KV), 8); mbar_init(BAR(B_XFREE), 8); mbar_init(BAR(B_XFREE + 1), 8); mbar_init(BAR(B_DONE), 10 + 2 * PSTEP); mbar_init(BAR(B_RT), 1);
      } else if (warp == 13) {
#pragma unroll
        for (int i = B_PART; i < B_X; i++) mbar_init(BAR(i), 1);
#pragma unroll
        for (int i = 0; i < 4; i++) mbar_expect(BAR(B_PART + i), 4096 - (i & 1) * 1024);
        if (rank) mbar_expect(BAR(B_HALO), 3584);
      } else if (warp == 14) {
#pragma unroll
        for (int i = B_ORDY; i < B_EMPTY; i++) mbar_init(BAR(i), i < B_FULL2 ? 1 : 2);
        mbar_arrive(BAR(B_EMPTY2)); mbar_arrive(BAR(B_EMPTY2 + 1));
      } else {
#pragma unroll
        for (int i = B_EMPTY; i < B_KV; i++) mbar_init(BAR(i), 4);
      }
      asm volatile("fence.mbarrier_init.release.cluster;" ::: "memory");
    }
    __syncwarp();
    asm volatile("barrier.cluster.arrive.relaxed.aligned;" ::: "memory");
    asm volatile("barrier.cluster.wait.acquire.aligned;" ::: "memory");
    if (warp == 13) {
      const uint32_t epoch = *(volatile uint32_t*)&gs->flag[(F_EPOCH + blockIdx.x) * 8] + 1;
      if (rank == 0) {
        mbar_wait_lim(BAR(B_KV), 0);
        if (tb == 0) {
#pragma unroll 1
          for (int c = lane; c < 224; c += 32) sts128(sb + (c < 112 ? OFF_K : OFF_V - 1792) + c * 16, make_uint4(0, 0, 0, 0));
          fence_async_smem();
          __syncwarp();
          if (lane == 0) mbar_arrive(BAR(B_HALO));
        } else {
          const uint32_t* f = &gs->flag[(F_HALO + (tb - 1) * 8 + j) * 8];
          int it = 0;
          while ((int32_t)(ld_flag(f) - epoch) < 0) { if (++it > (1 << 20)) __trap(); }
          fence_async_global();
          if (lane == 0) mbar_expect(BAR(B_HALO), 3584);
          __syncwarp();
          if (lane < 2) bulk_g2s(sb + OFF_K + lane * KVB, gs->halo + ((tb - 1) * 8 + j) * 224 + lane * 112, 1792, BAR(B_HALO));
          if (lane == 0) TS(55);
        }
      }
      const int box = lane < 2 ? 12 + lane : lane - 2;
      const uint32_t* flag = &gs->flag[(lane < 14 ? F_H + (T2 * 2 + rank) * 14 + box : (lane < 16 ? F_O + 2 * T2 - 14 + lane : F_W)) * 8];
      const uint32_t target = epoch * (lane < 2 ? 4 : (lane < 14 ? 2 : (lane < 16 ? 8 : 128)));
      mbar_wait_lim(BAR(B_GO), 0);
      bool pend = lane < 17;
      int it = 0;
      while (true) {
        if (pend && (int32_t)(ld_flag(flag) - target) >= 0) {
          fence_async_global();
          mbar_arrive(BAR(B_X + lane));
          pend = false;
          if (lane == 10) TS(57);
          if (lane == 13) TS(58);
        }
        if (!__any_sync(~0u, pend)) break;
        if (++it > (1 << 20)) __trap();
      }
      if (lane == 0) gs->flag[(F_EPOCH + blockIdx.x) * 8] = epoch;
      mbar_wait_lim(BAR(B_DONE), 0);
      FIN;
    } else if (lane == 0) {
      if (warp == 14) {
        mbar_wait(BAR(B_KV), 0);
        if (rank == 0) {
          const uint32_t hb = mapa(BAR(B_HALO), 1);
          bulk_s2s(mapa(sb + OFF_K, 1), sb + OFF_K + 16 * 896, 1792, hb);
          bulk_s2s(mapa(sb + OFF_V, 1), sb + OFF_V + 16 * 896, 1792, hb);
        } else {
          uint4* dst = gs->halo + (tb * 8 + j) * 224;
          bulk_s2g(dst, sb + OFF_K + 16 * 896, 1792);
          bulk_s2g(dst + 112, sb + OFF_V + 16 * 896, 1792);
          bulk_commit();
          bulk_wait0();
          flag_add(&gs->flag[(F_HALO + tb * 8 + j) * 8]);
          TS(60);
          mbar_arrive(BAR(B_KVFREE));
        }
        const int hb = (tb * 2 + (j >> 2)) * 14;
#pragma unroll 1
        for (int i = 0; i < 8; i++) {
          const int ps = i >> 1, w = i & 1;
          const int box = hb + (ps == 0 ? 12 + (qn >> 1) : 4 * (ps - 1) + qn);
          mbar_wait(BAR(B_H + w), ps & 1);
          bulk_s2g(gs->h + box * 1024 + w * 512 + (ps == 0 ? (qn & 1) * 256 : 0), sb + OFF_HS + w * 8192, ps == 0 ? 4096 : 8192);
          bulk_commit();
          bulk_wait0();
          flag_add(&gs->flag[(F_H + box) * 8]);
          mbar_arrive(BAR(B_HFREE + w));
          if (ps >= 2) TS(63 + 2 * (ps - 2) + w);
        }
        mbar_arrive_cluster(mapa(BAR(B_PFREE), rank ^ 1));
        mbar_arrive(BAR(B_DONE));
        FIN;
      } else {
        if (warp == 12)
        {
          if (warp == 12) TS(52);
          prefetch_map(&p.wg32); prefetch_map(&p.wu32); prefetch_map(rank ? &p.wu : &p.wg); prefetch_map(&p.xr);
          Ring rg{0, 1};
          const int fbase = (j >> 2) * 896;
          const int cq = j * 56 - (j & 1) * 8;
          int i = 0;
#pragma unroll 1
          for (int ps = 0; ps < 5; ps++) {
            const bool two = ps == 1 && rank == 1;
            const CUtensorMap* m = two ? &p.wg32 : (ps < 2 ? &p.wqkv : (rank ? &p.wu : &p.wg));
            const int c0 = two ? fbase + 768 + qn * 32 : (ps == 0 ? cq + D_ + D_ * rank : (ps == 1 ? cq : fbase + (4 * (ps - 2) + qn) * 64));
            if (ps == 1) mbar_wait(BAR(B_XFREE + 1), 0);
#pragma unroll 1
            for (int kt = 0; kt < 7; kt++, i++) {
              mbar_wait(BAR(B_EMPTY + rg.st), rg.ph);
              const uint32_t fb = BAR(B_FULL + rg.st), dst = sb + rg.st * STAGE + rank * 8192;
              mbar_expect(fb, STAGE);
              tma2d_mc(dst, m, fb, c0, kt * 64);
              if (two) tma2d_mc(dst + 4096, &p.wu32, fb, c0, kt * 64);
              rg.next();
              if (i == 35 - NST) mbar_arrive(BAR(B_GO));
            }
          }
          if (warp == 12) TS(53);
        }
      }
    } else {
      return;
    }
  }
  __syncwarp();
  if (((PMASK >> warp) & 1) && lane == 0) {
    const int isB = ~warp & 1;
    mbar_wait(BAR(B_WOK), 0);
    const int tile = isB ? 896 : 1024;
    const uint32_t src = isB ? (offsetof(Scratch, wd) >> 4) + (qn * 28 + rank * 14) * 896 : (T2 * 2 + rank) * 14 * 1024;
    const uint32_t osrc = (offsetof(Scratch, o) >> 4) + T2 * 2 * 56 * 64 + isB * 1024;
    int pr = PFIRST;
#pragma unroll 1
    for (int s = pr; s < 18; s += PSTEP) {
      int sl = 5 + isB + 2 * pr;
      if (sl >= 10) sl -= 10;
      const bool isO = !(s & 14);
      const bool last = isO && (s & isB);
      const uint4* from = gs->h + (isO ? osrc + (s >> 4) * 3584 + (s & 1) * 2048 : src + (s < 4 ? 10 + s : s - 4) * tile);
      if (isO || !isB) mbar_wait(BAR(isO ? B_ORDY + (s >> 4) : B_X - 2 + s), !isO);
      mbar_wait(BAR(B_EMPTY + 5), 0);
      mbar_wait(BAR(s < 5 ? B_EMPTY + sl : B_EMPTY2 + pr), s < 5 ? sl < 5 : (s >= 10 && s < 15));
      const int bytes = isO ? (last ? 8192 : STAGE) : tile * 16;
      mbar_expect(BAR(B_FULL2 + pr), last ? 8192 + 7168 : bytes);
      bulk_g2s(sb + sl * STAGE, from, bytes, BAR(B_FULL2 + pr));
      if (last) tma2d(sb + sl * STAGE + 8192, &p.xr, BAR(B_FULL2 + pr), qn * 112 + rank * 56, T2 * 128 + (s >> 4) * 64);
      if (!isB) { if (s == 0) TS(56); if (s == 12) TS(61); if (s == 15) TS(62); if (s == 17) TS(59); }
      pr += PSTEP;
      if (pr >= 5) pr -= 5;
    }
    mbar_arrive(BAR(B_DONE));
  }
#undef BAR
}

typedef CUresult (*EncFn)(CUtensorMap*, CUtensorMapDataType, cuuint32_t, void*, const cuuint64_t*, const cuuint64_t*,
                          const cuuint32_t*, const cuuint32_t*, CUtensorMapInterleave, CUtensorMapSwizzle,
                          CUtensorMapL2promotion, CUtensorMapFloatOOBfill);

void enc2d(EncFn enc, CUtensorMap* m, const void* ptr, int cols, int rows, int bc, int br, CUtensorMapSwizzle sw) {
  cuuint64_t gd[2] = {(cuuint64_t)cols, (cuuint64_t)rows};
  cuuint64_t gs[1] = {(cuuint64_t)cols * 2};
  cuuint32_t bd[2] = {(cuuint32_t)bc, (cuuint32_t)br}, es[2] = {1, 1};
  enc(m, CU_TENSOR_MAP_DATA_TYPE_BFLOAT16, 2, const_cast<void*>(ptr), gd, gs, bd, es, CU_TENSOR_MAP_INTERLEAVE_NONE, sw,
      CU_TENSOR_MAP_L2_PROMOTION_L2_128B, CU_TENSOR_MAP_FLOAT_OOB_FILL_NONE);
}

}

extern "C" void kernel_launch(void* const* d_in, const int* in_sizes, int n_in, void* d_out, int out_size) {
  static EncFn enc = nullptr;
  static Scratch* gs = nullptr;
  if (!enc) {
    cudaGetSymbolAddress((void**)&gs, g_s);
    void* fn = nullptr;
    cudaDriverEntryPointQueryResult qr;
    cudaGetDriverEntryPoint("cuTensorMapEncodeTiled", &fn, cudaEnableDefault, &qr);
    enc = (EncFn)fn;
    cudaFuncSetAttribute(fused_kernel, cudaFuncAttributeMaxDynamicSharedMemorySize, SMEM_BYTES);
  }
  Params p;
  enc2d(enc, &p.xm, d_in[0], D_, S_, 64, 64, CU_TENSOR_MAP_SWIZZLE_128B);
  enc2d(enc, &p.wqkv, d_in[1], 3 * D_, D_, 64, 64, CU_TENSOR_MAP_SWIZZLE_128B);
  enc2d(enc, &p.wg, d_in[4], F_, D_, 64, 64, CU_TENSOR_MAP_SWIZZLE_128B);
  enc2d(enc, &p.wu, d_in[5], F_, D_, 64, 64, CU_TENSOR_MAP_SWIZZLE_128B);
  enc2d(enc, &p.wg32, d_in[4], F_, D_, 32, 64, CU_TENSOR_MAP_SWIZZLE_64B);
  enc2d(enc, &p.wu32, d_in[5], F_, D_, 32, 64, CU_TENSOR_MAP_SWIZZLE_64B);
  enc2d(enc, &p.wdm, d_in[6], D_, F_, 112, 64, CU_TENSOR_MAP_SWIZZLE_NONE);
  enc2d(enc, &p.wom, d_in[2], D_, D_, 112, 64, CU_TENSOR_MAP_SWIZZLE_NONE);
  enc2d(enc, &p.xr, d_in[0], D_, S_, 56, 64, CU_TENSOR_MAP_SWIZZLE_NONE);
  fused_kernel<<<128, 512, SMEM_BYTES>>>(gs, (uint4*)d_out, (const uint4*)d_in[0], (const uint4*)d_in[1], p);
}
```

```cpp
#include <cuda_runtime.h>
#include <cuda_bf16.h>
#include <cuda.h>
#include <stdint.h>
#include <stddef.h>

namespace {

constexpr int S_ = 2048, D_ = 448, F_ = 1792;
constexpr int NST = 10;
constexpr int STAGE = 16384;
constexpr int KVB = 18 * 896;
constexpr int OFF_K = NST * STAGE;
constexpr int OFF_V = OFF_K + KVB;
constexpr int OFF_Q = OFF_V + KVB;
constexpr int OFF_HS = OFF_K + 50176;
constexpr int OFF_WOB = OFF_K;
constexpr int OFF_PART = OFF_HS;
constexpr int OFF_BAR = OFF_HS + 16384;
constexpr int SMEM_BYTES = OFF_BAR + 1024;
constexpr int B_FULL = 0, B_HFREE = 10  , B_PART = 12  , B_HALO = 16, B_GO = 17, B_PFREE = 18,
              B_X = 19  , B_ORDY = 33  , B_WOK = 35, B_KVFREE = 36, B_WOB = 37, B_STG = 38,
              B_FULL2 = 39  , B_EMPTY2 = 44  ,
              B_EMPTY = 49, B_Q = 59  , B_H = 61  ,
              B_KV = 63, B_XFREE = 64  , B_DONE = 66, B_RT = 67;
#define WOB0
#define LEAD 10
#define TOP 14
#define SQ 0
#define XP 0
#define IL 0
#define OR 0
#define LAG0 6
#define LAGP4 5
#define PD1 1500
#define PD2 0
#define PSTEP 1
#define PMASK 0x9000
#define PFIRST 0
#define LAGA 6
#define LAGB 6

struct Params {
  CUtensorMap xm, wqkv, wg, wu, wg32, wu32, wdm, wom, xr;
};

struct Scratch {
  uint4 h[S_ * F_ / 8];
  uint4 o[S_ * D_ / 8];
  uint4 wd[F_ * D_ / 8];
  uint4 wo[D_ * D_ / 8];
  uint4 halo[16 * 8 * 224];
  uint32_t flag[(448 + 32 + 1 + 128 + 128) * 8];
};
constexpr int F_H = 0, F_O = 448, F_W = 480, F_HALO = 481, F_EPOCH = 609;
__device__ Scratch g_s;
#define TS(slot)
#define TG(slot)
#define TSW(slot)
#define FIN return

#define SW(b, ph) mbar_wait(b, ph)
#define SDUMP(slot)
__device__ __forceinline__ uint32_t s2u(const void* p) { return (uint32_t)__cvta_generic_to_shared(p); }
__device__ __forceinline__ void mbar_init(uint32_t b, int c) { asm volatile("mbarrier.init.shared::cta.b64 [%0], %1;" ::"r"(b), "r"(c) : "memory"); }
__device__ __forceinline__ void mbar_expect(uint32_t b, int bytes) { asm volatile("mbarrier.arrive.expect_tx.shared::cta.b64 _, [%0], %1;" ::"r"(b), "r"(bytes) : "memory"); }
__device__ __forceinline__ void mbar_arrive(uint32_t b) { asm volatile("mbarrier.arrive.shared::cta.b64 _, [%0];" ::"r"(b) : "memory"); }
__device__ __forceinline__ void mbar_arrive_cluster(uint32_t b) { asm volatile("mbarrier.arrive.shared::cluster.b64 _, [%0];" ::"r"(b) : "memory"); }
__device__ __forceinline__ uint32_t mapa(uint32_t a, uint32_t r) { uint32_t o; asm volatile("mapa.shared::cluster.u32 %0, %1, %2;" : "=r"(o) : "r"(a), "r"(r)); return o; }
__device__ __forceinline__ void mbar_wait(uint32_t b, uint32_t ph) {
  asm volatile("{\n.reg .pred p;\nW: mbarrier.try_wait.parity.shared::cta.b64 p, [%0], %1;\n@!p bra W;\n}" ::"r"(b), "r"(ph) : "memory");
}
__device__ __forceinline__ void mbar_wait_lim(uint32_t b, uint32_t ph) {
  uint32_t ok;
  int it = 0;
  do {
    if (++it > (1 << 18)) __trap();
    asm volatile("{.reg .pred p; mbarrier.try_wait.parity.shared::cta.b64 p, [%1], %2; selp.u32 %0,1,0,p;}" : "=r"(ok) : "r"(b), "r"(ph) : "memory");
  } while (!ok);
}
__device__ __forceinline__ uint32_t ld_flag(const uint32_t* f) { uint32_t v; asm volatile("ld.relaxed.gpu.global.u32 %0, [%1];" : "=r"(v) : "l"(f) : "memory"); return v; }
__device__ __forceinline__ void flag_add(uint32_t* f) { asm volatile("red.relaxed.gpu.global.add.u32 [%0], 1;" ::"l"(f) : "memory"); }
__device__ __forceinline__ void fence_async_smem() { asm volatile("fence.proxy.async.shared::cta;" ::: "memory"); }
__device__ __forceinline__ void fence_async_global() { asm volatile("fence.proxy.async.global;" ::: "memory"); }

__device__ __forceinline__ void tma2d(uint32_t dst, const CUtensorMap* m, uint32_t bar, int c0, int c1) {
  asm volatile("cp.async.bulk.tensor.2d.shared::cluster.global.mbarrier::complete_tx::bytes [%0], [%1, {%3,%4}], [%2];" ::"r"(dst), "l"(m), "r"(bar), "r"(c0), "r"(c1) : "memory");
}
__device__ __forceinline__ void tma2d_mc(uint32_t dst, const CUtensorMap* m, uint32_t bar, int c0, int c1) {
  asm volatile("cp.async.bulk.tensor.2d.shared::cluster.global.mbarrier::complete_tx::bytes.multicast::cluster [%0], [%1, {%3,%4}], [%2], %5;" ::"r"(dst), "l"(m), "r"(bar), "r"(c0), "r"(c1), "h"((uint16_t)3) : "memory");
}
__device__ __forceinline__ void bulk_g2s(uint32_t dst, const void* src, int bytes, uint32_t bar) {
  asm volatile("cp.async.bulk.shared::cluster.global.mbarrier::complete_tx::bytes [%0], [%1], %2, [%3];" ::"r"(dst), "l"(src), "r"(bytes), "r"(bar) : "memory");
}
__device__ __forceinline__ void bulk_s2g(void* dst, uint32_t src, int bytes) {
  asm volatile("cp.async.bulk.global.shared::cta.bulk_group [%0], [%1], %2;" ::"l"(dst), "r"(src), "r"(bytes) : "memory");
}
__device__ __forceinline__ void bulk_s2s(uint32_t dst, uint32_t src, int bytes, uint32_t bar) {
  asm volatile("cp.async.bulk.shared::cluster.shared::cta.mbarrier::complete_tx::bytes [%0], [%1], %2, [%3];" ::"r"(dst), "r"(src), "r"(bytes), "r"(bar) : "memory");
}
__device__ __forceinline__ void bulk_commit() { asm volatile("cp.async.bulk.commit_group;" ::: "memory"); }
__device__ __forceinline__ void bulk_wait0() { asm volatile("cp.async.bulk.wait_group 0;" ::: "memory"); }
__device__ __forceinline__ void l2_prefetch(const void* p, int bytes) { asm volatile("cp.async.bulk.prefetch.L2.global [%0], %1;" ::"l"(p), "r"(bytes) : "memory"); }
__device__ __forceinline__ void delay(uint32_t cycles) {
  uint32_t c0, c1;
  asm volatile("mov.u32 %0, %%clock;" : "=r"(c0));
  do { asm volatile("mov.u32 %0, %%clock;" : "=r"(c1)); } while (c1 - c0 < cycles);
}
__device__ __forceinline__ void prefetch_map(const CUtensorMap* m) { asm volatile("prefetch.tensormap [%0];" ::"l"(m) : "memory"); }

__device__ __forceinline__ void ldsm4(uint32_t* r, uint32_t a) { asm volatile("ldmatrix.sync.aligned.m8n8.x4.shared.b16 {%0,%1,%2,%3}, [%4];" : "=r"(r[0]), "=r"(r[1]), "=r"(r[2]), "=r"(r[3]) : "r"(a) : "memory"); }
__device__ __forceinline__ void stsm4(uint32_t a, uint32_t r0, uint32_t r1, uint32_t r2, uint32_t r3) { asm volatile("stmatrix.sync.aligned.m8n8.x4.shared.b16 [%0], {%1,%2,%3,%4};" ::"r"(a), "r"(r0), "r"(r1), "r"(r2), "r"(r3) : "memory"); }
__device__ __forceinline__ void stsm2(uint32_t a, uint32_t r0, uint32_t r1) { asm volatile("stmatrix.sync.aligned.m8n8.x2.shared.b16 [%0], {%1,%2};" ::"r"(a), "r"(r0), "r"(r1) : "memory"); }
__device__ __forceinline__ uint32_t pack2(float lo, float hi) { uint32_t r; asm("cvt.rn.bf16x2.f32 %0, %1, %2;" : "=r"(r) : "f"(hi), "f"(lo)); return r; }
__device__ __forceinline__ float bf_lo(uint32_t v) { return __uint_as_float(v << 16); }
__device__ __forceinline__ float bf_hi(uint32_t v) { return __uint_as_float(v & 0xffff0000u); }
__device__ __forceinline__ float rbf(float v) { return bf_lo(pack2(v, 0.f)); }
__device__ __forceinline__ uint32_t sub2(uint32_t a, uint32_t b) { uint32_t r; asm("sub.rn.bf16x2 %0, %1, %2;" : "=r"(r) : "r"(a), "r"(b)); return r; }
__device__ __forceinline__ uint32_t add2(uint32_t a, uint32_t b) { uint32_t r; asm("add.rn.bf16x2 %0, %1, %2;" : "=r"(r) : "r"(a), "r"(b)); return r; }
__device__ __forceinline__ uint32_t mul2(uint32_t a, uint32_t b) { uint32_t r; asm("mul.rn.bf16x2 %0, %1, %2;" : "=r"(r) : "r"(a), "r"(b)); return r; }
__device__ __forceinline__ float ex2(float v) { float r; asm("ex2.approx.ftz.f32 %0, %1;" : "=f"(r) : "f"(v)); return r; }
__device__ __forceinline__ float tanh_approx(float v) { float r; asm("tanh.approx.f32 %0, %1;" : "=f"(r) : "f"(v)); return r; }
__device__ __forceinline__ float sqrt_approx(float v) { float r; asm("sqrt.approx.ftz.f32 %0, %1;" : "=f"(r) : "f"(v)); return r; }
__device__ __forceinline__ float rcp(float v) { float r; asm("rcp.approx.ftz.f32 %0, %1;" : "=f"(r) : "f"(v)); return r; }
__device__ __forceinline__ void lds128v(uint32_t* v, uint32_t a) { asm volatile("ld.shared.v4.u32 {%0,%1,%2,%3}, [%4];" : "=r"(v[0]), "=r"(v[1]), "=r"(v[2]), "=r"(v[3]) : "r"(a) : "memory"); }
__device__ __forceinline__ void sts128(uint32_t a, uint4 v) { asm volatile("st.shared.v4.u32 [%0], {%1,%2,%3,%4};" ::"r"(a), "r"(v.x), "r"(v.y), "r"(v.z), "r"(v.w) : "memory"); }

__device__ __forceinline__ void wg_fence() { asm volatile("wgmma.fence.sync.aligned;" ::: "memory"); }
__device__ __forceinline__ void wg_commit() { asm volatile("wgmma.commit_group.sync.aligned;" ::: "memory"); }
template <int N> __device__ __forceinline__ void wg_wait() { asm volatile("wgmma.wait_group.sync.aligned %0;" ::"n"(N) : "memory"); }
template <int N> __device__ __forceinline__ void reg_fence(float* d) {
#pragma unroll
  for (int i = 0; i < N; i++) asm volatile("" : "+f"(d[i])::"memory");
}
template <int N> __device__ __forceinline__ void zero(float* d) {
#pragma unroll
  for (int i = 0; i < N; i++) d[i] = 0.f;
}
__device__ __forceinline__ uint64_t mkdesc(uint32_t addr, uint32_t lbo, uint32_t sbo, uint32_t sw) {
  return (uint64_t)((addr & 0x3FFFF) >> 4) | ((uint64_t)(lbo >> 4) << 16) | ((uint64_t)(sbo >> 4) << 32) | ((uint64_t)sw << 62);
}

__device__ __forceinline__ void wgmma_rs_n56(float* d, const uint32_t* a, uint64_t db, int sd) {
  asm volatile("{\n.reg .pred p;\nsetp.ne.b32 p, %33, 0;\nwgmma.mma_async.sync.aligned.m64n56k16.f32.bf16.bf16 {%0,%1,%2,%3,%4,%5,%6,%7,%8,%9,%10,%11,%12,%13,%14,%15,%16,%17,%18,%19,%20,%21,%22,%23,%24,%25,%26,%27}, {%28,%29,%30,%31}, %32, p, 1, 1, 1;\n}\n"
    : "+f"(d[0]),"+f"(d[1]),"+f"(d[2]),"+f"(d[3]),"+f"(d[4]),"+f"(d[5]),"+f"(d[6]),"+f"(d[7]),"+f"(d[8]),"+f"(d[9]),"+f"(d[10]),"+f"(d[11]),"+f"(d[12]),"+f"(d[13]),"+f"(d[14]),"+f"(d[15]),"+f"(d[16]),"+f"(d[17]),"+f"(d[18]),"+f"(d[19]),"+f"(d[20]),"+f"(d[21]),"+f"(d[22]),"+f"(d[23]),"+f"(d[24]),"+f"(d[25]),"+f"(d[26]),"+f"(d[27])
    : "r"(a[0]),"r"(a[1]),"r"(a[2]),"r"(a[3]),"l"(db),"r"(sd));
}
__device__ __forceinline__ void wgmma_rs_n64(float* d, const uint32_t* a, uint64_t db, int sd) {
  asm volatile("{\n.reg .pred p;\nsetp.ne.b32 p, %37, 0;\nwgmma.mma_async.sync.aligned.m64n64k16.f32.bf16.bf16 {%0,%1,%2,%3,%4,%5,%6,%7,%8,%9,%10,%11,%12,%13,%14,%15,%16,%17,%18,%19,%20,%21,%22,%23,%24,%25,%26,%27,%28,%29,%30,%31}, {%32,%33,%34,%35}, %36, p, 1, 1, 1;\n}\n"
    : "+f"(d[0]),"+f"(d[1]),"+f"(d[2]),"+f"(d[3]),"+f"(d[4]),"+f"(d[5]),"+f"(d[6]),"+f"(d[7]),"+f"(d[8]),"+f"(d[9]),"+f"(d[10]),"+f"(d[11]),"+f"(d[12]),"+f"(d[13]),"+f"(d[14]),"+f"(d[15]),"+f"(d[16]),"+f"(d[17]),"+f"(d[18]),"+f"(d[19]),"+f"(d[20]),"+f"(d[21]),"+f"(d[22]),"+f"(d[23]),"+f"(d[24]),"+f"(d[25]),"+f"(d[26]),"+f"(d[27]),"+f"(d[28]),"+f"(d[29]),"+f"(d[30]),"+f"(d[31])
    : "r"(a[0]),"r"(a[1]),"r"(a[2]),"r"(a[3]),"l"(db),"r"(sd));
}
__device__ __forceinline__ void wgmma_rs_n128(float* d, const uint32_t* a, uint64_t db, int sd) {
  asm volatile("{\n.reg .pred p;\nsetp.ne.b32 p, %69, 0;\nwgmma.mma_async.sync.aligned.m64n128k16.f32.bf16.bf16 {%0,%1,%2,%3,%4,%5,%6,%7,%8,%9,%10,%11,%12,%13,%14,%15,%16,%17,%18,%19,%20,%21,%22,%23,%24,%25,%26,%27,%28,%29,%30,%31,%32,%33,%34,%35,%36,%37,%38,%39,%40,%41,%42,%43,%44,%45,%46,%47,%48,%49,%50,%51,%52,%53,%54,%55,%56,%57,%58,%59,%60,%61,%62,%63}, {%64,%65,%66,%67}, %68, p, 1, 1, 1;\n}\n"
    : "+f"(d[0]),"+f"(d[1]),"+f"(d[2]),"+f"(d[3]),"+f"(d[4]),"+f"(d[5]),"+f"(d[6]),"+f"(d[7]),"+f"(d[8]),"+f"(d[9]),"+f"(d[10]),"+f"(d[11]),"+f"(d[12]),"+f"(d[13]),"+f"(d[14]),"+f"(d[15]),"+f"(d[16]),"+f"(d[17]),"+f"(d[18]),"+f"(d[19]),"+f"(d[20]),"+f"(d[21]),"+f"(d[22]),"+f"(d[23]),"+f"(d[24]),"+f"(d[25]),"+f"(d[26]),"+f"(d[27]),"+f"(d[28]),"+f"(d[29]),"+f"(d[30]),"+f"(d[31]),"+f"(d[32]),"+f"(d[33]),"+f"(d[34]),"+f"(d[35]),"+f"(d[36]),"+f"(d[37]),"+f"(d[38]),"+f"(d[39]),"+f"(d[40]),"+f"(d[41]),"+f"(d[42]),"+f"(d[43]),"+f"(d[44]),"+f"(d[45]),"+f"(d[46]),"+f"(d[47]),"+f"(d[48]),"+f"(d[49]),"+f"(d[50]),"+f"(d[51]),"+f"(d[52]),"+f"(d[53]),"+f"(d[54]),"+f"(d[55]),"+f"(d[56]),"+f"(d[57]),"+f"(d[58]),"+f"(d[59]),"+f"(d[60]),"+f"(d[61]),"+f"(d[62]),"+f"(d[63])
    : "r"(a[0]),"r"(a[1]),"r"(a[2]),"r"(a[3]),"l"(db),"r"(sd));
}
__device__ __forceinline__ void wgmma_ss_n112(float* d, uint64_t da, uint64_t db, int sd) {
  asm volatile("{\n.reg .pred p;\nsetp.ne.b32 p, %58, 0;\nwgmma.mma_async.sync.aligned.m64n112k16.f32.bf16.bf16 {%0,%1,%2,%3,%4,%5,%6,%7,%8,%9,%10,%11,%12,%13,%14,%15,%16,%17,%18,%19,%20,%21,%22,%23,%24,%25,%26,%27,%28,%29,%30,%31,%32,%33,%34,%35,%36,%37,%38,%39,%40,%41,%42,%43,%44,%45,%46,%47,%48,%49,%50,%51,%52,%53,%54,%55}, %56, %57, p, 1, 1, 0, 1;\n}\n"
    : "+f"(d[0]),"+f"(d[1]),"+f"(d[2]),"+f"(d[3]),"+f"(d[4]),"+f"(d[5]),"+f"(d[6]),"+f"(d[7]),"+f"(d[8]),"+f"(d[9]),"+f"(d[10]),"+f"(d[11]),"+f"(d[12]),"+f"(d[13]),"+f"(d[14]),"+f"(d[15]),"+f"(d[16]),"+f"(d[17]),"+f"(d[18]),"+f"(d[19]),"+f"(d[20]),"+f"(d[21]),"+f"(d[22]),"+f"(d[23]),"+f"(d[24]),"+f"(d[25]),"+f"(d[26]),"+f"(d[27]),"+f"(d[28]),"+f"(d[29]),"+f"(d[30]),"+f"(d[31]),"+f"(d[32]),"+f"(d[33]),"+f"(d[34]),"+f"(d[35]),"+f"(d[36]),"+f"(d[37]),"+f"(d[38]),"+f"(d[39]),"+f"(d[40]),"+f"(d[41]),"+f"(d[42]),"+f"(d[43]),"+f"(d[44]),"+f"(d[45]),"+f"(d[46]),"+f"(d[47]),"+f"(d[48]),"+f"(d[49]),"+f"(d[50]),"+f"(d[51]),"+f"(d[52]),"+f"(d[53]),"+f"(d[54]),"+f"(d[55])
    : "l"(da),"l"(db),"r"(sd));
}
__device__ __forceinline__ void wgmma_ss_n56(float* d, uint64_t da, uint64_t db, int sd) {
  asm volatile("{\n.reg .pred p;\nsetp.ne.b32 p, %30, 0;\nwgmma.mma_async.sync.aligned.m64n56k16.f32.bf16.bf16 {%0,%1,%2,%3,%4,%5,%6,%7,%8,%9,%10,%11,%12,%13,%14,%15,%16,%17,%18,%19,%20,%21,%22,%23,%24,%25,%26,%27}, %28, %29, p, 1, 1, 0, 1;\n}\n"
    : "+f"(d[0]),"+f"(d[1]),"+f"(d[2]),"+f"(d[3]),"+f"(d[4]),"+f"(d[5]),"+f"(d[6]),"+f"(d[7]),"+f"(d[8]),"+f"(d[9]),"+f"(d[10]),"+f"(d[11]),"+f"(d[12]),"+f"(d[13]),"+f"(d[14]),"+f"(d[15]),"+f"(d[16]),"+f"(d[17]),"+f"(d[18]),"+f"(d[19]),"+f"(d[20]),"+f"(d[21]),"+f"(d[22]),"+f"(d[23]),"+f"(d[24]),"+f"(d[25]),"+f"(d[26]),"+f"(d[27])
    : "l"(da),"l"(db),"r"(sd));
}
__device__ __forceinline__ void wgmma_ssk_n80(float* d, uint64_t da, uint64_t db, int sd) {
  asm volatile("{\n.reg .pred p;\nsetp.ne.b32 p, %42, 0;\nwgmma.mma_async.sync.aligned.m64n80k16.f32.bf16.bf16 {%0,%1,%2,%3,%4,%5,%6,%7,%8,%9,%10,%11,%12,%13,%14,%15,%16,%17,%18,%19,%20,%21,%22,%23,%24,%25,%26,%27,%28,%29,%30,%31,%32,%33,%34,%35,%36,%37,%38,%39}, %40, %41, p, 1, 1, 0, 0;\n}\n"
    : "+f"(d[0]),"+f"(d[1]),"+f"(d[2]),"+f"(d[3]),"+f"(d[4]),"+f"(d[5]),"+f"(d[6]),"+f"(d[7]),"+f"(d[8]),"+f"(d[9]),"+f"(d[10]),"+f"(d[11]),"+f"(d[12]),"+f"(d[13]),"+f"(d[14]),"+f"(d[15]),"+f"(d[16]),"+f"(d[17]),"+f"(d[18]),"+f"(d[19]),"+f"(d[20]),"+f"(d[21]),"+f"(d[22]),"+f"(d[23]),"+f"(d[24]),"+f"(d[25]),"+f"(d[26]),"+f"(d[27]),"+f"(d[28]),"+f"(d[29]),"+f"(d[30]),"+f"(d[31]),"+f"(d[32]),"+f"(d[33]),"+f"(d[34]),"+f"(d[35]),"+f"(d[36]),"+f"(d[37]),"+f"(d[38]),"+f"(d[39])
    : "l"(da),"l"(db),"r"(sd));
}
__device__ __forceinline__ void wgmma_rs_n32(float* d, const uint32_t* a, uint64_t db, int sd) {
  asm volatile("{\n.reg .pred p;\nsetp.ne.b32 p, %21, 0;\nwgmma.mma_async.sync.aligned.m64n32k16.f32.bf16.bf16 {%0,%1,%2,%3,%4,%5,%6,%7,%8,%9,%10,%11,%12,%13,%14,%15}, {%16,%17,%18,%19}, %20, p, 1, 1, 1;\n}\n"
    : "+f"(d[0]),"+f"(d[1]),"+f"(d[2]),"+f"(d[3]),"+f"(d[4]),"+f"(d[5]),"+f"(d[6]),"+f"(d[7]),"+f"(d[8]),"+f"(d[9]),"+f"(d[10]),"+f"(d[11]),"+f"(d[12]),"+f"(d[13]),"+f"(d[14]),"+f"(d[15])
    : "r"(a[0]),"r"(a[1]),"r"(a[2]),"r"(a[3]),"l"(db),"r"(sd));
}

constexpr float LOG2E = 1.4426950408889634f;

__device__ __forceinline__ float swiglu(float g, float u, float hr) {
  const float z = g * hr, w = (u * hr) * z;
  return fmaf(w, tanh_approx(z), w);
}
__device__ __forceinline__ uint32_t fma2(uint32_t a, uint32_t b, uint32_t c) { uint32_t r; asm("fma.rn.bf16x2 %0, %1, %2, %3;" : "=r"(r) : "r"(a), "r"(b), "r"(c)); return r; }
__device__ __forceinline__ uint32_t gate2(float a0, float a1, uint32_t pv) {
  const float z0 = a0 + bf_lo(pv), z1 = a1 + bf_hi(pv);
  return pack2(fmaf(z0, tanh_approx(z0), z0), fmaf(z1, tanh_approx(z1), z1));
}

__device__ __forceinline__ void mma16(float* c, const uint32_t* a, uint32_t b0, uint32_t b1) {
  asm volatile("mma.sync.aligned.m16n8k16.row.col.f32.bf16.bf16.f32 {%0,%1,%2,%3}, {%4,%5,%6,%7}, {%8,%9}, {%0,%1,%2,%3};"
      : "+f"(c[0]), "+f"(c[1]), "+f"(c[2]), "+f"(c[3]) : "r"(a[0]), "r"(a[1]), "r"(a[2]), "r"(a[3]), "r"(b0), "r"(b1));
}
__device__ __forceinline__ void mma8(float* c, const uint32_t* a, uint32_t b) {
  asm volatile("mma.sync.aligned.m16n8k8.row.col.f32.bf16.bf16.f32 {%0,%1,%2,%3}, {%4,%5}, {%6}, {%0,%1,%2,%3};"
      : "+f"(c[0]), "+f"(c[1]), "+f"(c[2]), "+f"(c[3]) : "r"(a[0]), "r"(a[1]), "r"(b));
}
__device__ __forceinline__ void bar7(uint32_t dep) {
  asm volatile("{.reg .pred p; setp.eq.u32 p, %0, 0; bar.red.or.pred p, 7, 256, p;}" ::"r"(dep) : "memory");
}
__device__ __forceinline__ float stdev(float mean, float sq) {
  return rbf(sqrt_approx(rbf(rbf(fmaxf(fmaf(-mean, mean, sq * (1.f / D_)), 0.f)) + 1e-5f)));
}

struct Ring {
  uint32_t st, ph;
  __device__ __forceinline__ void next() { if (++st == NST) { st = 0; ph ^= 1; } }
};

__global__ void __cluster_dims__(2, 1, 1) __launch_bounds__(512, 1) fused_kernel(Scratch* __restrict__ gs, uint4* __restrict__ out, const uint4* __restrict__ x_in, const uint4* __restrict__ wqkv_in, const __grid_constant__ Params p) {
  extern __shared__ __align__(1024) uint8_t smem[];
  const uint32_t sb = s2u(smem);
  const uint32_t bars = sb + OFF_BAR;
  if (threadIdx.x == 0) prefetch_map(&p.xm);
  if (threadIdx.x == 384) prefetch_map(&p.wqkv);
  const int tid = threadIdx.x, warp = __shfl_sync(~0u, tid >> 5, 0), lane = tid & 31;
  const int rank = blockIdx.x & 1, cid = blockIdx.x >> 1;
  if (tid == 0) { TG(0); TS(1); }
  if (warp < 12) asm volatile("barrier.cluster.arrive.relaxed.aligned;" ::: "memory");
#define BAR(i) (bars + 8 * (i))
  const uint4* xp = x_in + ((blockIdx.x & 120) + blockIdx.x) * 448;
  if (tid == 256) {
    if (!(TOP & 1)) l2_prefetch(xp, 7168);
    delay(PD1);
    l2_prefetch(xp + 3584, 7168);
    delay(PD2);
    if (blockIdx.x < 112) {
#pragma unroll 1
      for (int i = 0; i < 4; i++) l2_prefetch(wqkv_in + (blockIdx.x + 112 * i) * 168 + 56, 1792);
    }
  }
  int grp, j;
  if (cid < 4) { grp = 0; j = 4 + cid; }
  else if (cid < 36) { grp = (cid - 4) & 7; j = (cid - 4) >> 3; }
  else { j = ((cid - 36) * 37) >> 8; grp = 1 + (cid - 36) - 7 * j; j += 4; }
  const int tb = 2 * grp + rank;
  const int T2 = 2 * grp + (j >> 2);
  const int qn = j & 3;
  const int wg = warp >> 2;
    const uint32_t xs = sb + (wg == 0 ? OFF_K : 7 * STAGE);
  if (warp < 8)
    {
      const int w = warp & 3;
      const uint32_t b0 = BAR(B_X + wg * 7 + w);
      if (lane == 0) {
        mbar_init(b0, 1);
        if (w < 3) mbar_init(b0 + 32, 1);
        fence_async_smem();
        mbar_expect(b0, 8192);
        if (w < 3) mbar_expect(b0 + 32, 8192);
      }
      if (wg == 1 && !IL) asm volatile("bar.sync 4, 256;" ::: "memory");
      if (lane == 0) {
        tma2d(xs + w * 8192, &p.xm, b0, w * 64, tb * 128 + wg * 64);
        if (w < 3) tma2d(xs + (w + 4) * 8192 + (warp == 6 ? 57344 : 0), &p.xm, b0 + 32, (w + 4) * 64, tb * 128 + wg * 64);
      }
      TSW(2 + wg);
      if (wg == 0 || IL) asm volatile("bar.sync 4, 256;" ::: "memory");
    }
  if (warp < 12) {
  if (warp < 8) {
#if !(TOP & 8)
    const uint32_t xs = sb + (wg == 0 ? OFF_K : 7 * STAGE);
    {
      const int w = warp & 3;
      const uint32_t b0 = BAR(B_X + wg * 7 + w);
      if (lane == 0) {
        mbar_init(b0, 1);
        if (w < 3) mbar_init(b0 + 32, 1);
        fence_async_smem();
        mbar_expect(b0, 8192);
        if (w < 3) mbar_expect(b0 + 32, 8192);
      }
      if (wg == 1 && !IL) asm volatile("bar.sync 4, 256;" ::: "memory");
      if (lane == 0) {
        tma2d(xs + w * 8192, &p.xm, b0, w * 64, tb * 128 + wg * 64);
        if (w < 3) tma2d(xs + (w + 4) * 8192 + (warp == 6 ? 57344 : 0), &p.xm, b0 + 32, (w + 4) * 64, tb * 128 + wg * 64);
      }
      TSW(2 + wg);
      if (wg == 0 || IL) asm volatile("bar.sync 4, 256;" ::: "memory");
    }
#endif
    asm volatile("barrier.cluster.wait.acquire.aligned;" ::: "memory");
    asm volatile("setmaxnreg.inc.sync.aligned.u32 208;");
    const int g = lane >> 2, q = lane & 3;
    uint32_t a[112];
    uint32_t m0, m1;
    float mu0, mu1, k0, k1;
    {
      const uint32_t xa = xs + ((warp & 3) * 16 + (lane & 15)) * 128;
      float sq[4][4], sum[2][4];
      zero<16>(&sq[0][0]); zero<8>(&sum[0][0]);
      const uint32_t one = gridDim.y, nil = gridDim.z - 1;
      uint32_t sa[4][4], okn = 0;
#pragma unroll
      for (int h = 0; h < 4; h++) { sa[h][1] = 0x3f803f80u + nil * (2 * h + 1); sa[h][3] = 0x3f803f80u + nil * (2 * h + 2); }
#pragma unroll
      for (int kt = 0; kt < 8; kt++) {
        if (kt < 7) {
          mbar_wait(BAR(B_X + wg * 7 + kt), 0);
          if (kt == 0) TSW(6 + wg);
          if (kt == 6) TSW(8 + wg);
          const uint32_t xk = xa + kt * 8192 + ((kt == 6 && wg == 1) ? 57344 : 0);
#pragma unroll
          for (int ks = 0; ks < 4; ks++) ldsm4(&a[16 * kt + 4 * ks], xk + (((2 * ks + (lane >> 4)) ^ (lane & 7)) << 4));
        }
        if (kt > 0) {
#pragma unroll
          for (int ks = 0; ks < 4; ks++) {
            const uint32_t* f = &a[16 * kt - 16 + 4 * ks];
            mma16(sum[ks & 1], f, 0x3f803f80u, 0x3f803f80u);
            mma8(sq[0], f, f[0]); mma8(sq[1], f, f[1]); mma8(sq[2], f + 2, f[2]); mma8(sq[3], f + 2, f[3]);
          }
        }
      }
      if (lane < 2) mbar_arrive_cluster(mapa(BAR(B_XFREE + wg), lane));
      k0 = (g & 1) ? sq[0][1] + sq[2][1] : sq[0][0] + sq[2][0];
      k1 = (g & 1) ? sq[1][3] + sq[3][3] : sq[1][2] + sq[3][2];
      if (wg == 1) bar7(__float_as_uint(k0) ^ __float_as_uint(k1));
      mu0 = (sum[0][0] + sum[1][0]) * (1.f / D_); mu1 = (sum[0][2] + sum[1][2]) * (1.f / D_);
      m0 = pack2(mu0, mu0); m1 = pack2(mu1, mu1);
#pragma unroll
      for (int i = 0; i < 16; i++) a[i] = sub2(a[i], (i & 1) ? m1 : m0);
      k0 = __shfl_sync(~0u, k0, (lane & 28) + (g >> 1)); k1 = __shfl_sync(~0u, k1, (lane & 28) + (g >> 1));
      TSW(4 + wg);
    }
    const bool rel = (lane == 0) && ((warp & 3) < 2);
    uint32_t rel_base = mapa(bars, rank ^ (warp & 1)) + 8 * B_EMPTY;
    const uint64_t dB128 = mkdesc(sb, 8192, 1024, 1);
    const uint64_t dW = dB128 + (j & 1);
    float rs0, rs1;

    {
      float accK[28], accV[28];
      mbar_wait(BAR(B_FULL), 0);
      if (wg == 0) {
        uint32_t d = __float_as_uint(k0) | __float_as_uint(k1);
#pragma unroll
        for (int i = 0; i < 16; i++) d |= a[i];
        bar7(d);
      } else {
        asm volatile("bar.sync 1, 256;" ::: "memory");
      }
#pragma unroll
      for (int kt = 0; kt < 7; kt++) {
        if (kt > 0) SW(BAR(B_FULL + kt), 0);
        TSW(70 + 2 * kt + wg);
        wg_fence();
#pragma unroll
        for (int ks = 0; ks < 4; ks++) {
          wgmma_rs_n56(accK, &a[(kt * 4 + ks) * 4], dW + (kt * 1024 + ks * 128), kt | ks);
          wgmma_rs_n56(accV, &a[(kt * 4 + ks) * 4], dW + (kt * 1024 + 512 + ks * 128), kt | ks);
        }
        wg_commit();
        if (kt == LAG0 && wg == 0) asm volatile("bar.arrive 1, 256;" ::: "memory");
        if (kt == LAGB && wg == 1) asm volatile("bar.arrive 5, 256;" ::: "memory");
        if (kt < 6) {
#pragma unroll
          for (int i = (kt + 1) * 16; i < (kt + 2) * 16; i++) asm volatile("sub.rn.bf16x2 %0, %0, %1;" : "+r"(a[i]) : "r"((i & 1) ? m1 : m0));
        }
        if (kt > 0) { wg_wait<1>(); if (rel) mbar_arrive_cluster(rel_base + 8 * (kt - 1)); }
      }
      rs0 = rcp(stdev(mu0, k0)); rs1 = rcp(stdev(mu1, k1));
      asm volatile("" : "+f"(rs0), "+f"(rs1));
      wg_wait<0>();
      reg_fence<28>(accK); reg_fence<28>(accV);
      if (rel) mbar_arrive_cluster(rel_base + 8 * 6);
      mbar_wait(BAR(B_XFREE), 0);
      TSW(10 + wg); SDUMP(70 + wg);
      const uint32_t ka = sb + OFF_K + (lane >> 4) * KVB + (2 + 2 * warp + ((lane >> 3) & 1)) * 896 + (lane & 7) * 16;
#pragma unroll
      for (int c = 0; c < 7; c++)
        stsm4(ka + c * 128, pack2(accK[4 * c] * rs0, accK[4 * c + 1] * rs0), pack2(accK[4 * c + 2] * rs1, accK[4 * c + 3] * rs1),
              pack2(accV[4 * c] * rs0, accV[4 * c + 1] * rs0), pack2(accV[4 * c + 2] * rs1, accV[4 * c + 3] * rs1));
      fence_async_smem();
      __syncwarp();
      if (lane == 0) mbar_arrive(BAR(B_KV));
      TSW(12 + wg);
    }
    const float hr0 = 0.5f * rs0, hr1 = 0.5f * rs1;
    const uint32_t tile_off = (lane >> 4) * 1024 + ((warp & 3) * 16 + (lane & 15)) * 16;
    const uint32_t hs_st = sb + OFF_HS + wg * 8192 + tile_off;
    const int bar_mine = 5 - 4 * wg, bar_other = 1 + 4 * wg;

    {
      const uint64_t dB64 = mkdesc(sb + 8192, 4096, 512, 2);
      float accQ[28], accG[32];
      asm volatile("bar.sync %0, 256;" ::"r"(bar_mine) : "memory");
#pragma unroll
      for (int kt = 0; kt < 7; kt++) {
        const int st = (7 + kt) % 10;
        SW(BAR(B_FULL + st), kt >= 3);
        if (kt == 0) TSW(14 + wg);
        wg_fence();
#pragma unroll
        for (int ks = 0; ks < 4; ks++) {
          wgmma_rs_n56(accQ, &a[(kt * 4 + ks) * 4], dW + (st * 1024 + ks * 128), kt | ks);
          wgmma_rs_n64(accG, &a[(kt * 4 + ks) * 4], dB64 + (st * 1024 + ks * 64), kt | ks);
        }
        wg_commit();
        if (kt == LAGA) asm volatile("bar.arrive %0, 256;" ::"r"(bar_other) : "memory");
        if (kt > 0) { wg_wait<1>(); if (rel) mbar_arrive_cluster(rel_base + 8 * ((6 + kt) % 10)); }
      }
      wg_wait<0>();
      reg_fence<28>(accQ); reg_fence<32>(accG);
      if (rel) mbar_arrive_cluster(rel_base + 8 * 3);
      mbar_wait(BAR(B_STG), 0);
      TSW(16 + wg); SDUMP(72 + wg);
      const uint32_t qa = hs_st - (OFF_HS - OFF_Q);
      uint32_t qp[14];
#pragma unroll
      for (int c = 0; c < 7; c++) { qp[2 * c] = pack2(accQ[4 * c] * rs0, accQ[4 * c + 1] * rs0); qp[2 * c + 1] = pack2(accQ[4 * c + 2] * rs1, accQ[4 * c + 3] * rs1); }
      stsm4(qa, qp[0], qp[1], qp[2], qp[3]);
      stsm4(qa + 2048, qp[4], qp[5], q < 2 ? qp[6] : 0u, q < 2 ? qp[7] : 0u);
      stsm4(qa + 4096, q < 2 ? 0u : qp[6], q < 2 ? 0u : qp[7], qp[8], qp[9]);
      stsm4(qa + 6144, qp[10], qp[11], qp[12], qp[13]);
#pragma unroll
      for (int c = 0; c < 2; c++) {
        uint32_t hp[4];
#pragma unroll
        for (int e = 0; e < 2; e++) {
          const float* gg = &accG[8 * c + 4 * e]; const float* uu = &accG[16 + 8 * c + 4 * e];
          hp[2 * e] = pack2(swiglu(gg[0], uu[0], hr0), swiglu(gg[1], uu[1], hr0));
          hp[2 * e + 1] = pack2(swiglu(gg[2], uu[2], hr1), swiglu(gg[3], uu[3], hr1));
        }
        stsm4(hs_st + c * 2048, hp[0], hp[1], hp[2], hp[3]);
      }
      fence_async_smem();
      __syncwarp();
      if (lane < 2) mbar_arrive(BAR(B_Q + wg + 2 * lane));
      TSW(18 + wg);
    }

    Ring rg{4, 1};
#pragma unroll 1
    for (int c3 = 0; c3 < 3; c3++) {
      float acc[64];
      if (c3 == 2) rel_base = mapa(bars, rank) + 8 * B_EMPTY;
      mbar_wait(BAR(B_FULL + rg.st), rg.ph);
      asm volatile("bar.sync %0, 256;" ::"r"(bar_mine) : "memory");
      uint32_t prev = 0;
#pragma unroll
      for (int kt = 0; kt < 7; kt++) {
        if (kt > 0) SW(BAR(B_FULL + rg.st), rg.ph);
        if (kt == 0) TSW(20 + 6 * c3 + wg);
        const uint64_t db = dB128 + (uint64_t)(rg.st * (STAGE >> 4));
        wg_fence();
#pragma unroll
        for (int ks = 0; ks < 4; ks++) wgmma_rs_n128(acc, &a[(kt * 4 + ks) * 4], db + ks * 128, kt | ks);
        wg_commit();
        if (kt == LAGP4 || kt == LAGA) { if ((kt == LAGP4) == (c3 == 2 && wg == 0)) asm volatile("bar.arrive %0, 256;" ::"r"(bar_other) : "memory"); }
        if (kt > 0) { wg_wait<1>(); if (rel) mbar_arrive_cluster(rel_base + 8 * prev); }
        prev = rg.st; rg.next();
      }
      wg_wait<0>();
      reg_fence<64>(acc);
      if (rel) mbar_arrive_cluster(rel_base + 8 * prev);
      mbar_wait(BAR(B_HFREE + wg), c3 & 1);
      TSW(22 + 6 * c3 + wg); SDUMP(74 + 2 * c3 + wg);
#pragma unroll
      for (int c = 0; c < 4; c++) {
        uint32_t hp[4];
#pragma unroll
        for (int e = 0; e < 4; e++) { const int i = 8 * c + 2 * e; const float hr = (i & 2) ? hr1 : hr0; hp[e] = pack2(swiglu(acc[i], acc[32 + i], hr), swiglu(acc[i + 1], acc[33 + i], hr)); }
        stsm4(hs_st + c * 2048, hp[0], hp[1], hp[2], hp[3]);
      }
      fence_async_smem();
      __syncwarp();
      if (lane == 0) mbar_arrive(BAR(B_H + wg));
      TSW(24 + 6 * c3 + wg);
    }

    uint64_t dA = mkdesc(sb, 1024, 128, 0);
    const uint64_t dBn = mkdesc(sb, 128, 1024, 0);
    uint64_t dWo = dBn + (OFF_WOB >> 4);
    const bool rel2 = (tid & 127) == 0;
    float dacc[56], sacc[28];
    uint32_t xr[14];
    auto wo_step = [&](int k, int slot) { wgmma_ss_n56(sacc, dA + (((slot + (k >> 3)) % 10) * 1024 + (k & 7) * 128), dWo + ((k >> 2) * 448 + (k & 3) * 16), k); };
    auto load_x = [&](int slot) {
      const uint32_t xra = sb + slot * STAGE + 8192 + ((warp & 3) * 16 + (lane & 15)) * 112 + (lane >> 4) * 16;
#pragma unroll
      for (int c = 0; c < 3; c++) ldsm4(&xr[4 * c], xra + c * 32);
      asm volatile("ldmatrix.sync.aligned.m8n8.x2.shared.b16 {%0,%1}, [%2];" : "=r"(xr[12]), "=r"(xr[13]) : "r"(xra + 96) : "memory");
    };
    if (wg == 0) {
      mbar_wait(BAR(B_WOB), 0);
      mbar_wait(BAR(B_FULL2), 0);
      asm volatile("bar.sync 5, 256;" ::: "memory");
      TSW(112);
      wg_fence();
#pragma unroll
      for (int k = 0; k < 16; k++) wo_step(k, 5);
      wg_commit();
      mbar_wait(BAR(B_FULL2 + 1), 0);
      load_x(8);
      wg_fence();
      wo_step(16, 5);
      wg_commit();
      wg_wait<1>();
      if (rel2) mbar_arrive(BAR(B_EMPTY2));
      asm volatile("bar.arrive 1, 256;" ::: "memory");
#pragma unroll
      for (int k = 17; k < 28; k++) wo_step(k, 5);
      wg_commit();
      asm volatile("{.reg .pred p; setp.ne.u32 p, %1, 1; @p st.shared.u32 [%1], %0;}" ::"r"(xr[0] ^ xr[4] ^ xr[8] ^ xr[12]), "r"(gridDim.y) : "memory");
    } else {
      asm volatile("bar.sync 1, 256;" ::: "memory");
    }
    int pr = 2, ph = 0, prev = 1;
#pragma unroll 1
    for (int kt = 0; kt < 14; kt++) {
      SW(BAR(B_FULL2 + pr), ph);
      TSW(84 + 2 * kt + wg);
      const uint64_t da = dA + (uint32_t)((pr < 3 ? 5 + 2 * pr : 2 * pr - 5) * 1024 + wg * 512);
      const uint64_t db = dBn + (uint32_t)((pr < 2 ? 6 + 2 * pr : 2 * pr - 4) * 1024);
      if (kt == LEAD && wg == 1) asm volatile("bar.sync 6, 256;" ::: "memory");
      wg_fence();
#pragma unroll
      for (int ks = 0; ks < 4; ks++) wgmma_ss_n112(dacc, da + ks * 128, db + ks * 16, kt | ks);
      wg_commit();
      if (kt == 13 && wg == 0) asm volatile("bar.arrive 6, 256;" ::: "memory");
      wg_wait<1>();
      if (rel2 && kt >= wg) mbar_arrive(BAR(B_EMPTY2 + prev));
      prev = pr;
      if (++pr == 5) { pr = 0; ph ^= 1; }
    }
    {
      const uint32_t part = sb + OFF_PART + warp * 1792;
      const uint32_t dst = mapa(part, rank ^ 1) + lane * 16, pb = mapa(BAR(B_PART + 2 * wg), rank ^ 1);
      const uint32_t aLo = (uint32_t)dA, bLo = (uint32_t)dWo;
      auto wo1 = [&](int k) { wgmma_ss_n56(sacc, (dA >> 32 << 32) | (aLo + (((7 + (k >> 3)) % 10) * 1024 + (k & 7) * 128)), (dWo >> 32 << 32) | (bLo + ((k >> 2) * 448 + (k & 3) * 16)), k); };
      mbar_wait(BAR(B_PFREE), 0);
      wg_wait<0>();
      reg_fence<56>(dacc);
      TSW(38 + wg); SDUMP(80 + wg);
#pragma unroll
      for (int i = 0; i < 4; i++) {
        const float* d = &dacc[28 + 8 * i];
        if (i < 3)
          asm volatile("st.async.shared::cluster.mbarrier::complete_tx::bytes.v4.b32 [%0], {%1,%2,%3,%4}, [%5];"
                       ::"r"(dst + i * 512), "r"(pack2(d[0], d[1])), "r"(pack2(d[2], d[3])), "r"(pack2(d[4], d[5])), "r"(pack2(d[6], d[7])), "r"(pb + (i >> 1) * 8) : "memory");
        else
          asm volatile("st.async.shared::cluster.mbarrier::complete_tx::bytes.v2.b32 [%0], {%1,%2}, [%3];"
                       ::"r"(dst + 1536 - lane * 8), "r"(pack2(d[0], d[1])), "r"(pack2(d[2], d[3])), "r"(pb + 8) : "memory");
      }
      TSW(40 + wg);
      if (wg == 1) {
        mbar_wait(BAR(B_FULL2 + 1), 1);
        TSW(113);
        wg_fence();
#pragma unroll
        for (int k = 0; k < 16; k++) wo1(k);
        mbar_wait(BAR(B_FULL2 + 2), 1);
        wg_fence();
#pragma unroll
        for (int k = 16; k < 28; k++) wo1(k);
        wg_commit();
        TSW(117);
      }
      const uint32_t pl = part + lane * 16, oa = part + (lane & 15) * 112 + (lane >> 4) * 16;
      uint32_t gp[14];
      mbar_wait(BAR(B_PART + 2 * wg), 0);
      TSW(120 + wg);
      lds128v(&gp[0], pl); lds128v(&gp[4], pl + 512);
#pragma unroll
      for (int i = 0; i < 8; i++) gp[i] = gate2(dacc[2 * i], dacc[2 * i + 1], gp[i]);
      mbar_wait(BAR(B_PART + 2 * wg + 1), 0);
      TSW(118 + wg);
      lds128v(&gp[8], pl + 1024);
      asm volatile("ld.shared.v2.u32 {%0,%1}, [%2];" : "=r"(gp[12]), "=r"(gp[13]) : "r"(part + 1536 + lane * 8) : "memory");
#pragma unroll
      for (int i = 8; i < 14; i++) gp[i] = gate2(dacc[2 * i], dacc[2 * i + 1], gp[i]);
      if (wg == 1) {
        const uint32_t xra = oa + (8192 - OFF_PART - 4 * 1792);
#pragma unroll
        for (int c = 0; c < 3; c++) ldsm4(&xr[4 * c], xra + c * 32);
        asm volatile("ldmatrix.sync.aligned.m8n8.x2.shared.b16 {%0,%1}, [%2];" : "=r"(xr[12]), "=r"(xr[13]) : "r"(xra + 96) : "memory");
      }
      if (lane == 0) mbar_arrive(BAR(B_DONE));
      wg_wait<0>();
      reg_fence<28>(sacc);
      __syncwarp();
      TSW(42 + wg);
#pragma unroll
      for (int c = 0; c < 14; c++) xr[c] = fma2(pack2(sacc[2 * c], sacc[2 * c + 1]), gp[c], xr[c]);
#pragma unroll
      for (int c = 0; c < 3; c++) stsm4(oa + c * 32, xr[4 * c], xr[4 * c + 1], xr[4 * c + 2], xr[4 * c + 3]);
      stsm2(oa + 96, xr[12], xr[13]);
      __syncwarp();
      uint32_t y[16];
#pragma unroll
      for (int i = 0; i < 4; i++) lds128v(&y[4 * i], pl + i * 512);
#pragma unroll
      for (int i = 0; i < 4; i++) {
        const int c = lane + 32 * i;
        asm volatile("{.reg .pred p; setp.lt.u32 p, %5, 16; @p st.global.v4.u32 [%0], {%1,%2,%3,%4};}"
                     ::"l"(out + ((T2 * 128 + warp * 16) * 56 + qn * 14 + rank * 7 + ((c * 147) >> 10) * 49 + c)), "r"(y[4 * i]), "r"(y[4 * i + 1]), "r"(y[4 * i + 2]), "r"(y[4 * i + 3]), "r"(i < 3 ? 0 : lane) : "memory");
      }
    }
    TSW(44 + wg);
    FIN;
  } else {
    asm volatile("setmaxnreg.dec.sync.aligned.u32 72;");
    asm volatile("barrier.cluster.wait.acquire.aligned;" ::: "memory");
    const int w = warp & 3, g = lane >> 2, q = lane & 3;
    {
      const bool two = blockIdx.x < 12;
      if (tid == 256) {
        const int u = blockIdx.x;
        prefetch_map(&p.wdm); prefetch_map(&p.wom);
        mbar_wait(BAR(B_XFREE), 0);
        mbar_wait(BAR(B_XFREE + 1), 0);
        TS(124);
        mbar_expect(BAR(B_RT), two ? 28672 : 14336);
        tma2d(sb + OFF_Q, u < 112 ? &p.wdm : &p.wom, BAR(B_RT), (u & 3) * 112, ((u >> 2) - (u < 112 ? 0 : 28)) * 64);
        if (two) tma2d(sb + OFF_Q + 14336, &p.wom, BAR(B_RT), (u & 3) * 112, ((u >> 2) + 4) * 64);
      }
      const int row = tid & 63, c0 = ((tid >> 6) ^ (tid >> 2)) & 1;
      mbar_wait(BAR(B_RT), 0);
      TSW(125);
#pragma unroll 1
      for (uint32_t stg = sb + OFF_Q; stg <= sb + OFF_Q + two * 14336; stg += 14336) {
        uint32_t v[28];
#pragma unroll
        for (int i = 0; i < 7; i++) lds128v(&v[4 * i], stg + row * 224 + c0 * 16 + i * 32);
        asm volatile("bar.sync 2, 128;" ::: "memory");
#pragma unroll
        for (int i = 0; i < 7; i++) sts128(stg + c0 * 1024 + row * 16 + i * 2048, make_uint4(v[4 * i], v[4 * i + 1], v[4 * i + 2], v[4 * i + 3]));
      }
      fence_async_smem();
      asm volatile("bar.sync 2, 128;" ::: "memory");
      TSW(51);
      if (warp == 8) {
        const int u = blockIdx.x + (lane >> 1) * 128, e = lane & 1;
        if (u < 140) {
          uint4* dst = u < 112 ? gs->wd + ((u & 3) * 28 + (u >> 2)) * 896 + (e ^ (u >= 56)) * 448 : gs->wo + (2 * (u & 3) + e) * 3136 + ((u >> 2) - 28) * 448;
          bulk_s2g(dst, sb + OFF_Q + lane * 7168, 7168);
          bulk_commit();
        }
        asm volatile("cp.async.bulk.wait_group.read 0;" ::: "memory");
        __syncwarp();
        if (lane == 0) { mbar_arrive(BAR(B_STG)); TS(68); }
        bulk_wait0();
        __syncwarp();
        if (lane == 0) { flag_add(&gs->flag[F_W * 8]); TS(67); }
      }
    }
    const int par = g & 1;
    const float sl2 = 0.1889822365046136f * LOG2E;
    uint32_t o3a = 0, o3b = 0;
    mbar_wait(BAR(B_KV), 0);
    mbar_wait(BAR(B_HALO), 0);
    if (rank == 1 && tid == 256) mbar_arrive_cluster(mapa(BAR(B_KVFREE), 0));
#pragma unroll 1
    for (int it = 0; it < 4; it++) {
      const int mt = it >> 1, hh = it & 1;
      mbar_wait(BAR(B_Q + mt), 0);
      if (it == 3 && tid == 256) { bulk_wait0(); flag_add(&gs->flag[(F_O + 2 * tb) * 8]); }
      if (hh == 0) TSW(46 + 2 * mt);
      const uint64_t dQ = mkdesc(sb + OFF_Q, 1024, 128, 0) + (uint64_t)(mt * 512 + hh * 256);
      const uint64_t dK = mkdesc(sb + OFF_K, 128, 896, 0) + (uint64_t)(mt * 448 + hh * 24);
      const uint64_t dV = mkdesc(sb + OFF_V, 896, 128, 0) + (uint64_t)(mt * 448 + hh * 24);
      const int jmin = 16 - (tb * 128 + mt * 64 + w * 16);
      float s[40];
      wg_fence();
      wgmma_ssk_n80(s, dQ, dK, 0);
      wgmma_ssk_n80(s, dQ + 128, dK + 16, 1);
      wg_commit();
      wg_wait<0>();
      reg_fence<40>(s);
      float u[20], v[12], l[8];
#pragma unroll
      for (int i = 0; i < 20; i++) u[i] = par ? s[2 * i + 1] : s[2 * i];
#pragma unroll
      for (int i = 0; i < 12; i++) v[i] = (w & 2) ? u[i + 8] : u[i];
      float m0 = -INFINITY, m1 = -INFINITY;
#pragma unroll
      for (int n = 0; n < 4; n++) {
        const int jj = 8 * n + 2 * q + par;
        const uint32_t d0 = g + 16 - jj, d1 = d0 + 8;
        l[2 * n] = (n < 3 && jj >= jmin && d0 <= 14) ? ((w & 1) ? v[2 * n + 4] : v[2 * n]) : -INFINITY;
        l[2 * n + 1] = (n > 0 && jj >= jmin && d1 <= 14) ? ((w & 1) ? v[2 * n + 5] : v[2 * n + 1]) : -INFINITY;
        m0 = fmaxf(m0, l[2 * n]); m1 = fmaxf(m1, l[2 * n + 1]);
      }
      m0 = fmaxf(m0, __shfl_xor_sync(~0u, m0, 1)); m1 = fmaxf(m1, __shfl_xor_sync(~0u, m1, 1));
      m0 = fmaxf(m0, __shfl_xor_sync(~0u, m0, 2)); m1 = fmaxf(m1, __shfl_xor_sync(~0u, m1, 2));
      float z0 = 0.f, z1 = 0.f;
#pragma unroll
      for (int n = 0; n < 4; n++) {
        l[2 * n] = n < 3 ? ex2((l[2 * n] - m0) * sl2) : 0.f; l[2 * n + 1] = n > 0 ? ex2((l[2 * n + 1] - m1) * sl2) : 0.f;
        z0 += l[2 * n]; z1 += l[2 * n + 1];
      }
      z0 += __shfl_xor_sync(~0u, z0, 1); z1 += __shfl_xor_sync(~0u, z1, 1);
      z0 += __shfl_xor_sync(~0u, z0, 2); z1 += __shfl_xor_sync(~0u, z1, 2);
      const float i0 = rcp(z0), i1 = rcp(z1);
      uint32_t pf[8];
#pragma unroll
      for (int i = 0; i < 8; i++) pf[i] = (i == 1 || i == 6) ? 0u : pack2(l[i] * ((i & 1) ? i1 : i0), 0.f) << (16 * par);
      uint32_t pa[5][4];
#pragma unroll
      for (int k = 0; k < 5; k++)
#pragma unroll
        for (int r = 0; r < 4; r++) pa[k][r] = (k < 4 && k == w) ? pf[r] : ((k > 0 && k == w + 1) ? pf[4 + r] : 0u);
      float o[16];
      wg_fence();
#pragma unroll
      for (int k = 0; k < 5; k++) wgmma_rs_n32(o, pa[k], dV + k * 112, k);
      wg_commit();
      wg_wait<0>();
      reg_fence<16>(o);
      const uint32_t qa = sb + OFF_Q + mt * 8192 + hh * 3072 + (lane >> 4) * 1024 + (w * 16 + (lane & 15)) * 16;
      const bool keep = hh && q < 2;
      stsm4(qa, keep ? o3a : pack2(o[0], o[1]), keep ? o3b : pack2(o[2], o[3]), pack2(o[4], o[5]), pack2(o[6], o[7]));
      o3a = pack2(o[12], o[13]); o3b = pack2(o[14], o[15]);
      stsm4(qa + 2048, pack2(o[8], o[9]), pack2(o[10], o[11]), o3a, o3b);
      if (hh) {
        fence_async_smem();
        asm volatile("bar.sync 2, 128;" ::: "memory");
        if (tid == 256) {
          bulk_s2g(gs->o + ((tb * 2 + mt) * 56 + 7 * j) * 64, sb + OFF_Q + mt * 8192, 7168);
          bulk_commit();
        }
        TSW(47 + 2 * mt);
      }
    }
    if (lane != 0) return;
    if (warp == 8 || warp == 11) {
      const int skip = warp == 8 ? 40448 : 0;
      mbar_wait(BAR(B_WOK), 0);
      mbar_wait(BAR(B_KVFREE), 0);
      asm volatile("cp.async.bulk.wait_group.read 0;" ::: "memory");
      if (warp == 8) mbar_expect(BAR(B_WOB), 50176);
      bulk_g2s(sb + OFF_WOB + skip, gs->wo + (2 * qn + rank) * 3136 + (skip >> 4), warp == 8 ? 50176 - skip : 40448, BAR(B_WOB));
      if (warp == 8) {
        bulk_wait0();
        TS(50);
        flag_add(&gs->flag[(F_O + 2 * tb + 1) * 8]);
        mbar_arrive(BAR(B_DONE));
      }
    }
  }
  } else {
    asm volatile("setmaxnreg.dec.sync.aligned.u32 24;");
    if (lane == 0) {
      if (warp == 12) {
        prefetch_map(&p.wqkv);
#pragma unroll
        for (int i = 0; i < B_PART; i++) mbar_init(BAR(i), 1);
        mbar_init(BAR(B_KV), 8); mbar_init(BAR(B_XFREE), 8); mbar_init(BAR(B_XFREE + 1), 8); mbar_init(BAR(B_DONE), 10 + 2 * PSTEP); mbar_init(BAR(B_RT), 1);
      } else if (warp == 13) {
#pragma unroll
        for (int i = B_PART; i < B_X; i++) mbar_init(BAR(i), 1);
#pragma unroll
        for (int i = 0; i < 4; i++) mbar_expect(BAR(B_PART + i), 4096 - (i & 1) * 1024);
        if (rank) mbar_expect(BAR(B_HALO), 3584);
      } else if (warp == 14) {
#pragma unroll
        for (int i = B_ORDY; i < B_EMPTY; i++) mbar_init(BAR(i), i < B_FULL2 ? 1 : 2);
        mbar_arrive(BAR(B_EMPTY2)); mbar_arrive(BAR(B_EMPTY2 + 1));
      } else {
#pragma unroll
        for (int i = B_EMPTY; i < B_KV; i++) mbar_init(BAR(i), 4);
      }
      asm volatile("fence.mbarrier_init.release.cluster;" ::: "memory");
    }
    __syncwarp();
    asm volatile("barrier.cluster.arrive.relaxed.aligned;" ::: "memory");
    asm volatile("barrier.cluster.wait.acquire.aligned;" ::: "memory");
    if (warp == 13) {
      const uint32_t epoch = *(volatile uint32_t*)&gs->flag[(F_EPOCH + blockIdx.x) * 8] + 1;
      if (rank == 0) {
        mbar_wait_lim(BAR(B_KV), 0);
        if (tb == 0) {
#pragma unroll 1
          for (int c = lane; c < 224; c += 32) sts128(sb + (c < 112 ? OFF_K : OFF_V - 1792) + c * 16, make_uint4(0, 0, 0, 0));
          fence_async_smem();
          __syncwarp();
          if (lane == 0) mbar_arrive(BAR(B_HALO));
        } else {
          const uint32_t* f = &gs->flag[(F_HALO + (tb - 1) * 8 + j) * 8];
          int it = 0;
          while ((int32_t)(ld_flag(f) - epoch) < 0) { if (++it > (1 << 20)) __trap(); }
          fence_async_global();
          if (lane == 0) mbar_expect(BAR(B_HALO), 3584);
          __syncwarp();
          if (lane < 2) bulk_g2s(sb + OFF_K + lane * KVB, gs->halo + ((tb - 1) * 8 + j) * 224 + lane * 112, 1792, BAR(B_HALO));
          if (lane == 0) TS(55);
        }
      }
      const int box = lane < 2 ? 12 + lane : lane - 2;
      const uint32_t* flag = &gs->flag[(lane < 14 ? F_H + (T2 * 2 + rank) * 14 + box : (lane < 16 ? F_O + 2 * T2 - 14 + lane : F_W)) * 8];
      const uint32_t target = epoch * (lane < 2 ? 4 : (lane < 14 ? 2 : (lane < 16 ? 8 : 128)));
      mbar_wait_lim(BAR(B_GO), 0);
      bool pend = lane < 17;
      int it = 0;
      while (true) {
        if (pend && (int32_t)(ld_flag(flag) - target) >= 0) {
          fence_async_global();
          mbar_arrive(BAR(B_X + lane));
          pend = false;
          if (lane == 10) TS(57);
          if (lane == 13) TS(58);
        }
        if (!__any_sync(~0u, pend)) break;
        if (++it > (1 << 20)) __trap();
      }
      if (lane == 0) gs->flag[(F_EPOCH + blockIdx.x) * 8] = epoch;
      mbar_wait_lim(BAR(B_DONE), 0);
      FIN;
    } else if (lane == 0) {
      if (warp == 14) {
        mbar_wait(BAR(B_KV), 0);
        if (rank == 0) {
          const uint32_t hb = mapa(BAR(B_HALO), 1);
          bulk_s2s(mapa(sb + OFF_K, 1), sb + OFF_K + 16 * 896, 1792, hb);
          bulk_s2s(mapa(sb + OFF_V, 1), sb + OFF_V + 16 * 896, 1792, hb);
        } else {
          uint4* dst = gs->halo + (tb * 8 + j) * 224;
          bulk_s2g(dst, sb + OFF_K + 16 * 896, 1792);
          bulk_s2g(dst + 112, sb + OFF_V + 16 * 896, 1792);
          bulk_commit();
          bulk_wait0();
          flag_add(&gs->flag[(F_HALO + tb * 8 + j) * 8]);
          TS(60);
          mbar_arrive(BAR(B_KVFREE));
        }
        const int hb = (tb * 2 + (j >> 2)) * 14;
#pragma unroll 1
        for (int i = 0; i < 8; i++) {
          const int ps = i >> 1, w = i & 1;
          const int box = hb + (ps == 0 ? 12 + (qn >> 1) : 4 * (ps - 1) + qn);
          mbar_wait(BAR(B_H + w), ps & 1);
          bulk_s2g(gs->h + box * 1024 + w * 512 + (ps == 0 ? (qn & 1) * 256 : 0), sb + OFF_HS + w * 8192, ps == 0 ? 4096 : 8192);
          bulk_commit();
          bulk_wait0();
          flag_add(&gs->flag[(F_H + box) * 8]);
          mbar_arrive(BAR(B_HFREE + w));
          if (ps >= 2) TS(63 + 2 * (ps - 2) + w);
        }
        mbar_arrive_cluster(mapa(BAR(B_PFREE), rank ^ 1));
        mbar_arrive(BAR(B_DONE));
        FIN;
      } else {
        if (warp == 12)
        {
          if (warp == 12) TS(52);
          prefetch_map(&p.wg32); prefetch_map(&p.wu32); prefetch_map(rank ? &p.wu : &p.wg); prefetch_map(&p.xr);
          Ring rg{0, 1};
          const int fbase = (j >> 2) * 896;
          const int cq = j * 56 - (j & 1) * 8;
          int i = 0;
#pragma unroll 1
          for (int ps = 0; ps < 5; ps++) {
            const bool two = ps == 1 && rank == 1;
            const CUtensorMap* m = two ? &p.wg32 : (ps < 2 ? &p.wqkv : (rank ? &p.wu : &p.wg));
            const int c0 = two ? fbase + 768 + qn * 32 : (ps == 0 ? cq + D_ + D_ * rank : (ps == 1 ? cq : fbase + (4 * (ps - 2) + qn) * 64));
            if (ps == 1) mbar_wait(BAR(B_XFREE + 1), 0);
#pragma unroll 1
            for (int kt = 0; kt < 7; kt++, i++) {
              mbar_wait(BAR(B_EMPTY + rg.st), rg.ph);
              const uint32_t fb = BAR(B_FULL + rg.st), dst = sb + rg.st * STAGE + rank * 8192;
              mbar_expect(fb, STAGE);
              tma2d_mc(dst, m, fb, c0, kt * 64);
              if (two) tma2d_mc(dst + 4096, &p.wu32, fb, c0, kt * 64);
              rg.next();
              if (i == 35 - NST) mbar_arrive(BAR(B_GO));
            }
          }
          if (warp == 12) TS(53);
        }
      }
    } else {
      return;
    }
  }
  __syncwarp();
  if (((PMASK >> warp) & 1) && lane == 0) {
    const int isB = ~warp & 1;
    mbar_wait(BAR(B_WOK), 0);
    const int tile = isB ? 896 : 1024;
    const uint32_t src = isB ? (offsetof(Scratch, wd) >> 4) + (qn * 28 + rank * 14) * 896 : (T2 * 2 + rank) * 14 * 1024;
    const uint32_t osrc = (offsetof(Scratch, o) >> 4) + T2 * 2 * 56 * 64 + isB * 1024;
    int pr = PFIRST;
#pragma unroll 1
    for (int s = pr; s < 18; s += PSTEP) {
      int sl = 5 + isB + 2 * pr;
      if (sl >= 10) sl -= 10;
      const bool isO = !(s & 14);
      const bool last = isO && (s & isB);
      const uint4* from = gs->h + (isO ? osrc + (s >> 4) * 3584 + (s & 1) * 2048 : src + (s < 4 ? 10 + s : s - 4) * tile);
      if (isO || !isB) mbar_wait(BAR(isO ? B_ORDY + (s >> 4) : B_X - 2 + s), !isO);
      mbar_wait(BAR(B_EMPTY + 5), 0);
      mbar_wait(BAR(s < 5 ? B_EMPTY + sl : B_EMPTY2 + pr), s < 5 ? sl < 5 : (s >= 10 && s < 15));
      const int bytes = isO ? (last ? 8192 : STAGE) : tile * 16;
      mbar_expect(BAR(B_FULL2 + pr), last ? 8192 + 7168 : bytes);
      bulk_g2s(sb + sl * STAGE, from, bytes, BAR(B_FULL2 + pr));
      if (last) tma2d(sb + sl * STAGE + 8192, &p.xr, BAR(B_FULL2 + pr), qn * 112 + rank * 56, T2 * 128 + (s >> 4) * 64);
      if (!isB) { if (s == 0) TS(56); if (s == 12) TS(61); if (s == 15) TS(62); if (s == 17) TS(59); }
      pr += PSTEP;
      if (pr >= 5) pr -= 5;
    }
    mbar_arrive(BAR(B_DONE));
  }
#undef BAR
}

typedef CUresult (*EncFn)(CUtensorMap*, CUtensorMapDataType, cuuint32_t, void*, const cuuint64_t*, const cuuint64_t*,
                          const cuuint32_t*, const cuuint32_t*, CUtensorMapInterleave, CUtensorMapSwizzle,
                          CUtensorMapL2promotion, CUtensorMapFloatOOBfill);

void enc2d(EncFn enc, CUtensorMap* m, const void* ptr, int cols, int rows, int bc, int br, CUtensorMapSwizzle sw) {
  cuuint64_t gd[2] = {(cuuint64_t)cols, (cuuint64_t)rows};
  cuuint64_t gs[1] = {(cuuint64_t)cols * 2};
  cuuint32_t bd[2] = {(cuuint32_t)bc, (cuuint32_t)br}, es[2] = {1, 1};
  enc(m, CU_TENSOR_MAP_DATA_TYPE_BFLOAT16, 2, const_cast<void*>(ptr), gd, gs, bd, es, CU_TENSOR_MAP_INTERLEAVE_NONE, sw,
      CU_TENSOR_MAP_L2_PROMOTION_L2_128B, CU_TENSOR_MAP_FLOAT_OOB_FILL_NONE);
}

}

extern "C" void kernel_launch(void* const* d_in, const int* in_sizes, int n_in, void* d_out, int out_size) {
  static EncFn enc = nullptr;
  static Scratch* gs = nullptr;
  if (!enc) {
    cudaGetSymbolAddress((void**)&gs, g_s);
    void* fn = nullptr;
    cudaDriverEntryPointQueryResult qr;
    cudaGetDriverEntryPoint("cuTensorMapEncodeTiled", &fn, cudaEnableDefault, &qr);
    enc = (EncFn)fn;
    cudaFuncSetAttribute(fused_kernel, cudaFuncAttributeMaxDynamicSharedMemorySize, SMEM_BYTES);
  }
  Params p;
  enc2d(enc, &p.xm, d_in[0], D_, S_, 64, 64, CU_TENSOR_MAP_SWIZZLE_128B);
  enc2d(enc, &p.wqkv, d_in[1], 3 * D_, D_, 64, 64, CU_TENSOR_MAP_SWIZZLE_128B);
  enc2d(enc, &p.wg, d_in[4], F_, D_, 64, 64, CU_TENSOR_MAP_SWIZZLE_128B);
  enc2d(enc, &p.wu, d_in[5], F_, D_, 64, 64, CU_TENSOR_MAP_SWIZZLE_128B);
  enc2d(enc, &p.wg32, d_in[4], F_, D_, 32, 64, CU_TENSOR_MAP_SWIZZLE_64B);
  enc2d(enc, &p.wu32, d_in[5], F_, D_, 32, 64, CU_TENSOR_MAP_SWIZZLE_64B);
  enc2d(enc, &p.wdm, d_in[6], D_, F_, 112, 64, CU_TENSOR_MAP_SWIZZLE_NONE);
  enc2d(enc, &p.wom, d_in[2], D_, D_, 112, 64, CU_TENSOR_MAP_SWIZZLE_NONE);
  enc2d(enc, &p.xr, d_in[0], D_, S_, 56, 64, CU_TENSOR_MAP_SWIZZLE_NONE);
  fused_kernel<<<128, 512, SMEM_BYTES>>>(gs, (uint4*)d_out, (const uint4*)d_in[0], (const uint4*)d_in[1], p);
}
```
